```python
import torch

def _softmax(x, axis=-1):
    return torch.softmax(x, dim=axis)

def _gelu(x):
    return torch.nn.functional.gelu(x, approximate='tanh')

def _silu(x):
    return torch.nn.functional.silu(x)

def _sigmoid(x):
    return torch.sigmoid(x)

def _layernorm(x, axis=-1, eps=1e-05):
    m = x.mean(dim=axis, keepdim=True)
    v = x.var(dim=axis, keepdim=True, unbiased=False)
    return (x - m) / torch.sqrt(v + eps)

def _scatter_add(tgt, idx, src, axis=0):
    return tgt.clone().index_add_(axis, idx, src)

def _segment_sum(src, seg, n):
    out = torch.zeros((n,) + src.shape[1:], dtype=src.dtype)
    return out.index_add_(0, seg, src)

def _pad(x, pw):
    flat = tuple((v for pair in reversed(pw) for v in pair))
    return torch.nn.functional.pad(x, flat)
kernel_name = 'adaLN_cond__ssm_conv_h3__dense_activation_silu__prompt'

def setup_inputs():

    _w = lambda a: (lambda t: t.to(torch.bfloat16) if t.is_floating_point() else t)(torch.as_tensor(a))

    def _A_setup():
        B, S, D = (1, 2048, 512)
        ks = 4
        return {'q': _w((lambda *s: torch.randn(*s, dtype=torch.bfloat16) * 0.05)(B, S, D)), 'k': _w((lambda *s: torch.randn(*s, dtype=torch.bfloat16) * 0.8)(B, S, D)), 'v': _w((lambda *s: torch.randn(*s, dtype=torch.bfloat16) * 0.8)(B, S, D)), 'shift_k': _w((lambda *s: torch.randn(*s, dtype=torch.bfloat16) * 0.8)(D, ks) * 0.5), 'ssm_k': _w((lambda *s: torch.randn(*s, dtype=torch.bfloat16) * 0.8)(D, S) * (1.0 / S ** 0.5)), 'ssm_D': _w((lambda *s: torch.randn(*s, dtype=torch.bfloat16) * 0.8)(D))}
    _A_in = _A_setup()

    def _B_setup():
        B, S, D, F = (1, 2048, 512, 1792)
        return {'x': _w((lambda *s: torch.randn(*s, dtype=torch.bfloat16) * 0.05)(B, S, D)), 'w1': _w((lambda *s: torch.randn(*s, dtype=torch.bfloat16) * 3.2)(D, F) * D ** (-0.5)), 'w2': _w((lambda *s: torch.randn(*s, dtype=torch.bfloat16) * 0.8)(F, D) * F ** (-0.5))}
    _B_in = _B_setup()
    return {'A_q': _A_in['q'], 'A_k': _A_in['k'], 'A_v': _A_in['v'], 'A_shift_k': _A_in['shift_k'], 'A_ssm_k': _A_in['ssm_k'], 'A_ssm_D': _A_in['ssm_D'], 'B_x': _B_in['x'], 'B_w1': _B_in['w1'], 'B_w2': _B_in['w2'], 'c': _w((lambda *s: torch.randn(*s, dtype=torch.bfloat16) * 0.2)(1, 512) * 8.0), 'w_mod': _w((lambda *s: torch.randn(*s, dtype=torch.bfloat16) * 0.2)(512, 6 * 512) * 512 ** (-0.5) * 8.0)}

def reference(A_q, A_k, A_v, A_shift_k, A_ssm_k, A_ssm_D, B_x, B_w1, B_w2, c, w_mod):

    def _A_ref(q, k, v, shift_k, ssm_k, ssm_D):
        B, S, D = q.shape
        ks = shift_k.shape[-1]
        k_pad = _pad(k, ((0, 0), (ks - 1, 0), (0, 0)))
        k_shift = torch.zeros_like(k)
        for t in range(ks):
            k_shift = k_shift + k_pad[:, t:t + S, :] * shift_k[:, ks - 1 - t][None, None, :]
        kv = k_shift * v
        L = 2 * S
        kv_pad = _pad(kv, ((0, 0), (0, S), (0, 0)))
        kf_pad = _pad(ssm_k, ((0, 0), (0, S)))
        kv_f = (lambda x, axes=(-2, -1): torch.fft.rfft2(x.float(), dim=axes))(kv_pad[:, None, :, :], axes=(1, 2))
        kf_f = (lambda x, axes=(-2, -1): torch.fft.rfft2(x.float(), dim=axes))(kf_pad[:, None, :], axes=(1, 2))
        kf_f = (lambda x, *d: x.permute(*d))(kf_f, 1, 2, 0)
        y_f = kv_f * kf_f[None, :, :, :]
        y = (lambda x, s, axes=(-2, -1): torch.fft.irfft2(x, s=s, dim=axes).to(torch.bfloat16))(y_f, (1, L), axes=(1, 2))[:, 0, :S, :]
        y = y + kv * ssm_D[None, None, :]
        return q * y

    def _B_ref(x, w1, w2):
        h = torch.einsum('bsd,df->bsf', x, w1)
        h = _silu(h)
        out = torch.einsum('bsf,fd->bsd', h, w2)
        return out
    x = A_q
    mod = (_silu(c) @ w_mod).reshape(c.shape[0], 6, 1, -1)
    sa, ca, ga, sb, cb, gb = (mod[:, 0].clone(), mod[:, 1].clone(), mod[:, 2].clone(), mod[:, 3].clone(), mod[:, 4].clone(), mod[:, 5].clone())
    h = _layernorm(x, axis=-1) * (1 + ca) + sa
    x = x + ga * _A_ref(h, A_k, A_v, A_shift_k, A_ssm_k, A_ssm_D)
    h = _layernorm(x, axis=-1) * (1 + cb) + sb
    x = x + gb * _B_ref(h, B_w1, B_w2)
    return x
```

```cpp
#include <cuda_runtime.h>
#include <cuda_bf16.h>
#include <stdint.h>

#define S_LEN 2048
#define D_DIM 512
#define F_DIM 1792

typedef __nv_bfloat16 bf16;

__device__ float g_mod[6 * D_DIM];
__device__ bf16 g_kv[S_LEN * D_DIM];
__device__ bf16 g_y2[S_LEN * D_DIM];
__device__ bf16 g_x1[S_LEN * D_DIM];
__device__ bf16 g_h2[S_LEN * D_DIM];
__device__ bf16 g_h1[S_LEN * F_DIM];

__device__ __forceinline__ float bfr(float x) { return __bfloat162float(__float2bfloat16_rn(x)); }
__device__ __forceinline__ float b2f(bf16 x) { return __bfloat162float(x); }

__global__ void k_mod(const bf16* c, const bf16* w_mod) {
    int j = blockIdx.x * blockDim.x + threadIdx.x;
    if (j >= 6 * D_DIM) return;
    float acc = 0.f;
    for (int i = 0; i < D_DIM; i++) {
        float cv = b2f(c[i]);
        float s = bfr(cv / (1.f + __expf(-cv)));
        acc += s * b2f(w_mod[i * (6 * D_DIM) + j]);
    }
    g_mod[j] = bfr(acc);
}

__global__ void k_kv(const bf16* k, const bf16* v, const bf16* shift_k) {
    int idx = blockIdx.x * blockDim.x + threadIdx.x;
    if (idx >= S_LEN * D_DIM) return;
    int s = idx / D_DIM, d = idx % D_DIM;
    float acc = 0.f;
    for (int t = 0; t < 4; t++) {
        int ss = s - 3 + t;
        float kk = ss >= 0 ? b2f(k[ss * D_DIM + d]) : 0.f;
        float p = bfr(kk * b2f(shift_k[d * 4 + (3 - t)]));
        acc = bfr(acc + p);
    }
    g_kv[idx] = __float2bfloat16_rn(acc * b2f(v[idx]));
}

__global__ void k_conv(const bf16* ssm_k, const bf16* ssm_D) {
    int d = blockIdx.x;
    __shared__ float su[S_LEN];
    __shared__ float sk[S_LEN];
    for (int s = threadIdx.x; s < S_LEN; s += blockDim.x) {
        su[s] = b2f(g_kv[s * D_DIM + d]);
        sk[s] = b2f(ssm_k[d * S_LEN + s]);
    }
    __syncthreads();
    for (int s = threadIdx.x; s < S_LEN; s += blockDim.x) {
        float acc = 0.f;
        for (int j = 0; j <= s; j++) acc += su[j] * sk[s - j];
        float y = bfr(acc);
        y = bfr(y + bfr(su[s] * b2f(ssm_D[d])));
        g_y2[s * D_DIM + d] = __float2bfloat16_rn(y);
    }
}

__device__ float block_sum(float v, float* red) {
    for (int o = 16; o > 0; o >>= 1) v += __shfl_xor_sync(0xffffffff, v, o);
    int w = threadIdx.x >> 5, l = threadIdx.x & 31;
    __syncthreads();
    if (l == 0) red[w] = v;
    __syncthreads();
    float t = 0.f;
    for (int i = 0; i < (int)(blockDim.x >> 5); i++) t += red[i];
    return t;
}

__global__ void k_mid(const bf16* x) {
    __shared__ float red[8];
    int s = blockIdx.x;
    float xv[4];
    for (int i = 0; i < 4; i++) xv[i] = b2f(x[s * D_DIM + threadIdx.x * 4 + i]);
    float sum = xv[0] + xv[1] + xv[2] + xv[3];
    float mean_f = block_sum(sum, red) / D_DIM;
    float sq = 0.f;
    for (int i = 0; i < 4; i++) sq += (xv[i] - mean_f) * (xv[i] - mean_f);
    float var_f = block_sum(sq, red) / D_DIM;
    float m = bfr(mean_f), var = bfr(var_f);
    float den = bfr(sqrtf(bfr(var + 1e-5f)));
    float x1v[4];
    for (int i = 0; i < 4; i++) {
        int d = threadIdx.x * 4 + i;
        float sa = g_mod[0 * D_DIM + d], ca = g_mod[1 * D_DIM + d], ga = g_mod[2 * D_DIM + d];
        float ln = bfr(bfr(xv[i] - m) / den);
        float h = bfr(bfr(ln * bfr(1.f + ca)) + sa);
        float a = bfr(h * b2f(g_y2[s * D_DIM + d]));
        x1v[i] = bfr(xv[i] + bfr(ga * a));
        g_x1[s * D_DIM + d] = __float2bfloat16_rn(x1v[i]);
    }
    sum = x1v[0] + x1v[1] + x1v[2] + x1v[3];
    mean_f = block_sum(sum, red) / D_DIM;
    sq = 0.f;
    for (int i = 0; i < 4; i++) sq += (x1v[i] - mean_f) * (x1v[i] - mean_f);
    var_f = block_sum(sq, red) / D_DIM;
    m = bfr(mean_f); var = bfr(var_f);
    den = bfr(sqrtf(bfr(var + 1e-5f)));
    for (int i = 0; i < 4; i++) {
        int d = threadIdx.x * 4 + i;
        float sb = g_mod[3 * D_DIM + d], cb = g_mod[4 * D_DIM + d];
        float ln = bfr(bfr(x1v[i] - m) / den);
        float h = bfr(bfr(ln * bfr(1.f + cb)) + sb);
        g_h2[s * D_DIM + d] = __float2bfloat16_rn(h);
    }
}

template <int MODE>
__global__ void k_gemm(const bf16* A, const bf16* B, bf16* C, int M, int N, int K) {
    __shared__ float sa[16][17], sb[16][17];
    int tx = threadIdx.x, ty = threadIdx.y;
    int row = blockIdx.y * 16 + ty, col = blockIdx.x * 16 + tx;
    float acc = 0.f;
    for (int k0 = 0; k0 < K; k0 += 16) {
        sa[ty][tx] = b2f(A[row * K + k0 + tx]);
        sb[ty][tx] = b2f(B[(k0 + ty) * N + col]);
        __syncthreads();
        for (int k = 0; k < 16; k++) acc += sa[ty][k] * sb[k][tx];
        __syncthreads();
    }
    if (MODE == 0) {
        float h = bfr(acc);
        float s = h / (1.f + __expf(-h));
        C[row * N + col] = __float2bfloat16_rn(s);
    } else {
        float o = bfr(acc);
        float gb = g_mod[5 * D_DIM + col];
        C[row * N + col] = __float2bfloat16_rn(b2f(g_x1[row * N + col]) + bfr(gb * o));
    }
}

extern "C" void kernel_launch(void* const* d_in, const int* in_sizes, int n_in,
                              void* d_out, int out_size) {
    const bf16* q = (const bf16*)d_in[0];
    const bf16* k = (const bf16*)d_in[1];
    const bf16* v = (const bf16*)d_in[2];
    const bf16* shift_k = (const bf16*)d_in[3];
    const bf16* ssm_k = (const bf16*)d_in[4];
    const bf16* ssm_D = (const bf16*)d_in[5];
    const bf16* w1 = (const bf16*)d_in[7];
    const bf16* w2 = (const bf16*)d_in[8];
    const bf16* c = (const bf16*)d_in[9];
    const bf16* w_mod = (const bf16*)d_in[10];
    bf16* out = (bf16*)d_out;

    k_mod<<<(6 * D_DIM + 127) / 128, 128>>>(c, w_mod);
    k_kv<<<(S_LEN * D_DIM + 255) / 256, 256>>>(k, v, shift_k);
    k_conv<<<D_DIM, 512>>>(ssm_k, ssm_D);
    k_mid<<<S_LEN, 128>>>(q);
    bf16 *h2, *h1;
    cudaGetSymbolAddress((void**)&h2, g_h2);
    cudaGetSymbolAddress((void**)&h1, g_h1);
    k_gemm<0><<<dim3(F_DIM / 16, S_LEN / 16), dim3(16, 16)>>>(h2, w1, h1, S_LEN, F_DIM, D_DIM);
    k_gemm<1><<<dim3(D_DIM / 16, S_LEN / 16), dim3(16, 16)>>>(h1, w2, out, S_LEN, D_DIM, F_DIM);
}
```

```cpp
#include <cuda_runtime.h>
#include <cuda.h>
#include <cuda_bf16.h>
#include <stdint.h>

#define S_LEN 2048
#define D_DIM 512
#define F_DIM 1792

typedef __nv_bfloat16 bf16;
typedef __nv_bfloat162 bf162;

__device__ float g_mod[6 * D_DIM];
__device__ bf16 g_y2T[D_DIM * S_LEN];
__device__ bf16 g_x1[S_LEN * D_DIM];
__device__ bf16 g_h2[S_LEN * D_DIM];
__device__ bf16 g_h1[S_LEN * F_DIM];

__device__ __forceinline__ float bfr(float x) { return __bfloat162float(__float2bfloat16_rn(x)); }
__device__ __forceinline__ float b2f(bf16 x) { return __bfloat162float(x); }
__device__ __forceinline__ uint32_t smem_u32(const void* p) { return (uint32_t)__cvta_generic_to_shared(p); }

constexpr int CONV_THREADS = 512;
constexpr int R_WORDS = 1064;
constexpr int R_BYTES = 2 * R_WORDS * 4;
constexpr int U_CHUNK = 656;
constexpr int U_BYTES = 8 * U_CHUNK;
constexpr int CH_BYTES = R_BYTES + U_BYTES;
constexpr int CONV_SMEM = 4 * CH_BYTES + 16 * 24 * 4;

__device__ __forceinline__ void wg_fence() { asm volatile("wgmma.fence.sync.aligned;" ::: "memory"); }
__device__ __forceinline__ void wg_commit() { asm volatile("wgmma.commit_group.sync.aligned;" ::: "memory"); }
template <int N> __device__ __forceinline__ void wg_wait() { asm volatile("wgmma.wait_group.sync.aligned %0;" ::"n"(N) : "memory"); }

template <int NT> struct ConvMMA;
template <> struct ConvMMA<1> {
    static __device__ __forceinline__ void run(float* d, uint32_t a0, uint32_t a1, uint32_t a2, uint32_t a3, uint64_t desc) {
        asm volatile("wgmma.mma_async.sync.aligned.m64n8k16.f32.bf16.bf16 {%0,%1,%2,%3}, {%4,%5,%6,%7}, %8, 1, 1, 1, 0;"
                     : "+f"(d[12]), "+f"(d[13]), "+f"(d[14]), "+f"(d[15])
                     : "r"(a0), "r"(a1), "r"(a2), "r"(a3), "l"(desc));
    }
};
template <> struct ConvMMA<2> {
    static __device__ __forceinline__ void run(float* d, uint32_t a0, uint32_t a1, uint32_t a2, uint32_t a3, uint64_t desc) {
        asm volatile("wgmma.mma_async.sync.aligned.m64n16k16.f32.bf16.bf16 {%0,%1,%2,%3,%4,%5,%6,%7}, {%8,%9,%10,%11}, %12, 1, 1, 1, 0;"
                     : "+f"(d[8]), "+f"(d[9]), "+f"(d[10]), "+f"(d[11]), "+f"(d[12]), "+f"(d[13]), "+f"(d[14]), "+f"(d[15])
                     : "r"(a0), "r"(a1), "r"(a2), "r"(a3), "l"(desc));
    }
};
template <> struct ConvMMA<3> {
    static __device__ __forceinline__ void run(float* d, uint32_t a0, uint32_t a1, uint32_t a2, uint32_t a3, uint64_t desc) {
        asm volatile("wgmma.mma_async.sync.aligned.m64n24k16.f32.bf16.bf16 {%0,%1,%2,%3,%4,%5,%6,%7,%8,%9,%10,%11}, {%12,%13,%14,%15}, %16, 1, 1, 1, 0;"
                     : "+f"(d[4]), "+f"(d[5]), "+f"(d[6]), "+f"(d[7]), "+f"(d[8]), "+f"(d[9]), "+f"(d[10]), "+f"(d[11]),
                       "+f"(d[12]), "+f"(d[13]), "+f"(d[14]), "+f"(d[15])
                     : "r"(a0), "r"(a1), "r"(a2), "r"(a3), "l"(desc));
    }
};
template <> struct ConvMMA<4> {
    static __device__ __forceinline__ void run(float* d, uint32_t a0, uint32_t a1, uint32_t a2, uint32_t a3, uint64_t desc) {
        asm volatile("wgmma.mma_async.sync.aligned.m64n32k16.f32.bf16.bf16 {%0,%1,%2,%3,%4,%5,%6,%7,%8,%9,%10,%11,%12,%13,%14,%15}, {%16,%17,%18,%19}, %20, 1, 1, 1, 0;"
                     : "+f"(d[0]), "+f"(d[1]), "+f"(d[2]), "+f"(d[3]), "+f"(d[4]), "+f"(d[5]), "+f"(d[6]), "+f"(d[7]),
                       "+f"(d[8]), "+f"(d[9]), "+f"(d[10]), "+f"(d[11]), "+f"(d[12]), "+f"(d[13]), "+f"(d[14]), "+f"(d[15])
                     : "r"(a0), "r"(a1), "r"(a2), "r"(a3), "l"(desc));
    }
};

__device__ __forceinline__ uint32_t lds32(uint32_t addr) {
    uint32_t v;
    asm volatile("ld.shared.u32 %0, [%1];" : "=r"(v) : "r"(addr));
    return v;
}

template <int NT>
__device__ __forceinline__ void conv_group(float* d, uint32_t rbase, uint32_t ubase, uint32_t* wA) {
    constexpr int A_LO = 8 * (4 - NT);
    constexpr uint64_t DESC_HI = ((uint64_t)(U_CHUNK >> 4) << 16) | ((uint64_t)(128 >> 4) << 32);
#pragma unroll 1
    for (int c = A_LO + 7; c >= A_LO; c -= 2) {
        uint32_t wB[9];
        uint32_t ub = ubase + (7 + A_LO - c) * 16;
        uint64_t da = DESC_HI | (uint64_t)((ub & 0x3FFFF) >> 4);
        wg_fence();
#pragma unroll
        for (int js = 0; js < 4; js++)
            ConvMMA<NT>::run(d, wA[2 * js + 1], wA[2 * js], wA[2 * js + 2], wA[2 * js + 1], da + (uint64_t)((2 * js * U_CHUNK) >> 4));
        wg_commit();
        {
            uint32_t ra = rbase - 128 * (c - 1) - 16;
#pragma unroll
            for (int m = 0; m < 9; m++) wB[m] = lds32(ra + 16 * m);
        }
        wg_fence();
#pragma unroll
        for (int js = 0; js < 4; js++)
            ConvMMA<NT>::run(d, wB[2 * js + 1], wB[2 * js], wB[2 * js + 2], wB[2 * js + 1], da + (uint64_t)((2 * js * U_CHUNK + 16) >> 4));
        wg_commit();
        wg_wait<1>();
        {
            uint32_t ra = rbase - 128 * (c - 2) - 16;
#pragma unroll
            for (int m = 0; m < 9; m++) wA[m] = lds32(ra + 16 * m);
        }
    }
    wg_wait<0>();
}

__global__ void __launch_bounds__(CONV_THREADS, 1)
k_conv(const bf16* __restrict__ k, const bf16* __restrict__ v, const bf16* __restrict__ shift_k,
       const bf16* __restrict__ ssm_k, const bf16* __restrict__ ssm_D,
       const bf16* __restrict__ cvec, const bf16* __restrict__ w_mod) {
    extern __shared__ __align__(128) uint8_t smem[];
    const int tid = threadIdx.x;
    const int d0 = blockIdx.x * 4;
    float* modred = (float*)(smem + 4 * CH_BYTES);
    const uint4* wmp = (const uint4*)(w_mod + (size_t)tid * (6 * D_DIM) + blockIdx.x * 24);
    uint4 wm0 = wmp[0], wm1 = wmp[1], wm2 = wmp[2];
    const float cvi = b2f(cvec[tid]);

    if (tid < 256) {
        const int s0 = tid * 8;
        uint2 kr[11], vr[8];
#pragma unroll
        for (int r = 0; r < 11; r++) {
            int s = s0 - 3 + r;
            kr[r] = s >= 0 ? *(const uint2*)(k + (size_t)s * D_DIM + d0) : make_uint2(0u, 0u);
        }
#pragma unroll
        for (int r = 0; r < 8; r++) vr[r] = *(const uint2*)(v + (size_t)(s0 + r) * D_DIM + d0);
        uint4 sk0 = *(const uint4*)(shift_k + d0 * 4);
        uint4 sk1 = *(const uint4*)(shift_k + d0 * 4 + 8);
        uint32_t tp[4][2];
        tp[0][0] = __byte_perm(sk0.x, sk0.z, 0x5410); tp[1][0] = __byte_perm(sk0.x, sk0.z, 0x7632);
        tp[2][0] = __byte_perm(sk0.y, sk0.w, 0x5410); tp[3][0] = __byte_perm(sk0.y, sk0.w, 0x7632);
        tp[0][1] = __byte_perm(sk1.x, sk1.z, 0x5410); tp[1][1] = __byte_perm(sk1.x, sk1.z, 0x7632);
        tp[2][1] = __byte_perm(sk1.y, sk1.w, 0x5410); tp[3][1] = __byte_perm(sk1.y, sk1.w, 0x7632);
        uint32_t kvp[8][2];
#pragma unroll
        for (int r = 0; r < 8; r++) {
#pragma unroll
            for (int h = 0; h < 2; h++) {
                auto K = [&](int rr) { uint32_t u = h ? kr[rr].y : kr[rr].x; return *(bf162*)&u; };
                auto T = [&](int j) { uint32_t u = tp[j][h]; return *(bf162*)&u; };
                uint32_t vv = h ? vr[r].y : vr[r].x;
                bf162 acc = __hmul2_rn(K(r), T(3));
                acc = __hadd2_rn(acc, __hmul2_rn(K(r + 1), T(2)));
                acc = __hadd2_rn(acc, __hmul2_rn(K(r + 2), T(1)));
                acc = __hadd2_rn(acc, __hmul2_rn(K(r + 3), T(0)));
                bf162 kvv = __hmul2_rn(acc, *(bf162*)&vv);
                kvp[r][h] = *(uint32_t*)&kvv;
            }
        }
        const int b = tid >> 3, jc = tid & 7;
#pragma unroll
        for (int ch = 0; ch < 4; ch++) {
            const int h = ch >> 1;
            const uint32_t sel = (ch & 1) ? 0x7632 : 0x5410;
            uint4 o;
            o.x = __byte_perm(kvp[0][h], kvp[1][h], sel);
            o.y = __byte_perm(kvp[2][h], kvp[3][h], sel);
            o.z = __byte_perm(kvp[4][h], kvp[5][h], sel);
            o.w = __byte_perm(kvp[6][h], kvp[7][h], sel);
            *(uint4*)(smem + ch * CH_BYTES + R_BYTES + jc * U_CHUNK + (7 + b) * 16) = o;
        }
    } else {
        const int t2 = tid - 256;
#pragma unroll
        for (int ch = 0; ch < 4; ch++) {
            const bf16* kk = ssm_k + (size_t)(d0 + ch) * S_LEN;
            const int G = t2;
            uint4 a = *(const uint4*)(kk + 8 * G);
            uint32_t pw = G > 0 ? ((uint32_t)(*(const uint16_t*)(kk + 8 * G - 1)) << 16) : 0u;
            uint4 c1, c0;
            c1.x = __byte_perm(a.w, 0, 0x1032); c1.y = __byte_perm(a.z, 0, 0x1032);
            c1.z = __byte_perm(a.y, 0, 0x1032); c1.w = __byte_perm(a.x, 0, 0x1032);
            c0.x = __byte_perm(a.w, a.z, 0x7610); c0.y = __byte_perm(a.z, a.y, 0x7610);
            c0.z = __byte_perm(a.y, a.x, 0x7610); c0.w = __byte_perm(a.x, pw, 0x7610);
            uint8_t* R = smem + ch * CH_BYTES;
            *(uint4*)(R + (1020 - 4 * G) * 4) = c0;
            *(uint4*)(R + R_WORDS * 4 + (1020 - 4 * G) * 4) = c1;
        }
        if (t2 < 80) {
            int ch = t2 / 20, r = t2 % 20;
            uint8_t* R = smem + ch * CH_BYTES;
            *(uint4*)(R + (r / 10) * R_WORDS * 4 + (1024 + 4 * (r % 10)) * 4) = make_uint4(0, 0, 0, 0);
        } else if (t2 < 80 + 4 * 8 * 7 && t2 >= 80) {
        }
        for (int i = t2; i < 4 * 8 * 7; i += 256) {
            int ch = i / 56, r = i % 56, jc = r / 7, row = r % 7;
            *(uint4*)(smem + ch * CH_BYTES + R_BYTES + jc * U_CHUNK + row * 16) = make_uint4(0, 0, 0, 0);
        }
    }
    asm volatile("fence.proxy.async.shared::cta;" ::: "memory");
    __syncthreads();

    const int wg = tid >> 7, w = (tid >> 5) & 3, lane = tid & 31, g = lane >> 2, t = lane & 3;
    const uint32_t chb = smem_u32(smem) + wg * CH_BYTES;
    const uint32_t rbase = chb + (g & 1) * (R_WORDS * 4) + 4 * (1023 - 8 * w - (g >> 1) + t);
    const uint32_t ubase = chb + R_BYTES;
    float d[16], d1[16], d2[16], d3[16];
#pragma unroll
    for (int i = 0; i < 16; i++) { d[i] = 0.f; d1[i] = 0.f; d2[i] = 0.f; d3[i] = 0.f; }
    uint32_t wv[9];
#pragma unroll
    for (int m = 0; m < 9; m++) wv[m] = lds32(rbase - 128 * 31 - 16 + 16 * m);
    conv_group<1>(d1, rbase, ubase, wv);
    conv_group<2>(d2, rbase, ubase, wv);
    conv_group<3>(d3, rbase, ubase, wv);
    conv_group<4>(d, rbase, ubase, wv);
#pragma unroll
    for (int i = 12; i < 16; i++) d[i] += d1[i];
#pragma unroll
    for (int i = 8; i < 16; i++) d[i] += d2[i];
#pragma unroll
    for (int i = 4; i < 16; i++) d[i] += d3[i];

    const int dch = d0 + wg;
    const float Dv = b2f(ssm_D[dch]);
    bf16* yo = g_y2T + (size_t)dch * S_LEN;
    const uint8_t* U = smem + wg * CH_BYTES + R_BYTES;
#pragma unroll
    for (int nt = 0; nt < 4; nt++) {
#pragma unroll
        for (int e = 0; e < 4; e++) {
            int i = 16 * w + g + (e >> 1) * 8;
            int a = 8 * nt + 2 * t + (e & 1);
            float u = b2f(*(const bf16*)(U + (i >> 3) * U_CHUNK + (7 + a) * 16 + (i & 7) * 2));
            float y = bfr(d[4 * nt + e]);
            y = y + bfr(u * Dv);
            yo[64 * a + i] = __float2bfloat16_rn(y);
        }
    }
    {
        const float sl = bfr(cvi / (1.f + __expf(-cvi)));
        uint32_t ww[12] = {wm0.x, wm0.y, wm0.z, wm0.w, wm1.x, wm1.y, wm1.z, wm1.w, wm2.x, wm2.y, wm2.z, wm2.w};
        float acc[24];
#pragma unroll
        for (int e = 0; e < 12; e++) {
            acc[2 * e] = sl * __uint_as_float(ww[e] << 16);
            acc[2 * e + 1] = sl * __uint_as_float(ww[e] & 0xffff0000u);
        }
#pragma unroll
        for (int j = 0; j < 24; j++) {
#pragma unroll
            for (int o = 16; o > 0; o >>= 1) acc[j] += __shfl_xor_sync(0xffffffffu, acc[j], o);
        }
        if ((tid & 31) == 0) {
#pragma unroll
            for (int j = 0; j < 24; j++) modred[(tid >> 5) * 24 + j] = acc[j];
        }
        __syncthreads();
        if (tid < 24) {
            float sum = 0.f;
#pragma unroll
            for (int wq = 0; wq < 16; wq++) sum += modred[wq * 24 + tid];
            g_mod[blockIdx.x * 24 + tid] = bfr(sum);
        }
    }
}

constexpr int MID_ROWS = 16;
__device__ __forceinline__ bf162 u2b(uint32_t u) { return *(bf162*)&u; }
__device__ __forceinline__ uint32_t b2u(bf162 b) { return *(uint32_t*)&b; }
__device__ __forceinline__ void row_stats(const uint32_t* xp, bf162& m2, float& rden) {
    float sum = 0.f;
#pragma unroll
    for (int i = 0; i < 8; i++) { float2 f = __bfloat1622float2(u2b(xp[i])); sum += f.x + f.y; }
#pragma unroll
    for (int o = 16; o > 0; o >>= 1) sum += __shfl_xor_sync(0xffffffffu, sum, o);
    const float mean = sum * (1.f / D_DIM);
    float sq = 0.f;
#pragma unroll
    for (int i = 0; i < 8; i++) { float2 f = __bfloat1622float2(u2b(xp[i])); sq += (f.x - mean) * (f.x - mean) + (f.y - mean) * (f.y - mean); }
#pragma unroll
    for (int o = 16; o > 0; o >>= 1) sq += __shfl_xor_sync(0xffffffffu, sq, o);
    const bf16 mb = __float2bfloat16_rn(mean);
    m2 = __halves2bfloat162(mb, mb);
    const float den = bfr(sqrtf(bfr(bfr(sq * (1.f / D_DIM)) + 1e-5f)));
    rden = 1.f / den;
}
__global__ void __launch_bounds__(512, 2) k_mid(const bf16* __restrict__ x) {
    __shared__ __align__(16) bf16 ys[MID_ROWS][D_DIM + 8];
    const int tid = threadIdx.x, lane = tid & 31, wid = tid >> 5;
    const int s0 = blockIdx.x * MID_ROWS;
    {
        const uint4* p = (const uint4*)(g_y2T + (size_t)tid * S_LEN + s0);
        uint4 a = p[0], b = p[1];
        const bf16* pa = (const bf16*)&a;
        const bf16* pb = (const bf16*)&b;
#pragma unroll
        for (int r = 0; r < 8; r++) { ys[r][tid] = pa[r]; ys[r + 8][tid] = pb[r]; }
    }
    const int s = s0 + wid;
    uint32_t xp[8];
    *(uint4*)xp = *(const uint4*)(x + (size_t)s * D_DIM + lane * 8);
    *(uint4*)(xp + 4) = *(const uint4*)(x + (size_t)s * D_DIM + 256 + lane * 8);
    uint32_t c1a[8], csa[8], cga[8], c1b[8], csb[8];
#pragma unroll
    for (int h = 0; h < 2; h++) {
#pragma unroll
        for (int q = 0; q < 4; q++) {
            const int d = h * 256 + lane * 8 + 2 * q;
            float2 sa = *(const float2*)(g_mod + d), ca = *(const float2*)(g_mod + D_DIM + d), ga = *(const float2*)(g_mod + 2 * D_DIM + d);
            float2 sb = *(const float2*)(g_mod + 3 * D_DIM + d), cb = *(const float2*)(g_mod + 4 * D_DIM + d);
            c1a[h * 4 + q] = b2u(__floats2bfloat162_rn(1.f + ca.x, 1.f + ca.y));
            csa[h * 4 + q] = b2u(__floats2bfloat162_rn(sa.x, sa.y));
            cga[h * 4 + q] = b2u(__floats2bfloat162_rn(ga.x, ga.y));
            c1b[h * 4 + q] = b2u(__floats2bfloat162_rn(1.f + cb.x, 1.f + cb.y));
            csb[h * 4 + q] = b2u(__floats2bfloat162_rn(sb.x, sb.y));
        }
    }
    bf162 m2; float rden;
    row_stats(xp, m2, rden);
    __syncthreads();
    uint32_t x1[8];
#pragma unroll
    for (int i = 0; i < 8; i++) {
        const int h = i >> 2, q = i & 3;
        uint32_t yv = *(const uint32_t*)(&ys[wid][h * 256 + lane * 8 + 2 * q]);
        bf162 xm = __hsub2_rn(u2b(xp[i]), m2);
        float2 f = __bfloat1622float2(xm);
        bf162 ln = __floats2bfloat162_rn(f.x * rden, f.y * rden);
        bf162 hh = __hadd2_rn(__hmul2_rn(ln, u2b(c1a[i])), u2b(csa[i]));
        bf162 a = __hmul2_rn(hh, u2b(yv));
        bf162 r = __hadd2_rn(u2b(xp[i]), __hmul2_rn(u2b(cga[i]), a));
        x1[i] = b2u(r);
    }
    *(uint4*)(g_x1 + (size_t)s * D_DIM + lane * 8) = *(uint4*)x1;
    *(uint4*)(g_x1 + (size_t)s * D_DIM + 256 + lane * 8) = *(uint4*)(x1 + 4);
    row_stats(x1, m2, rden);
    uint32_t h2[8];
#pragma unroll
    for (int i = 0; i < 8; i++) {
        bf162 xm = __hsub2_rn(u2b(x1[i]), m2);
        float2 f = __bfloat1622float2(xm);
        bf162 ln = __floats2bfloat162_rn(f.x * rden, f.y * rden);
        h2[i] = b2u(__hadd2_rn(__hmul2_rn(ln, u2b(c1b[i])), u2b(csb[i])));
    }
    *(uint4*)(g_h2 + (size_t)s * D_DIM + lane * 8) = *(uint4*)h2;
    *(uint4*)(g_h2 + (size_t)s * D_DIM + 256 + lane * 8) = *(uint4*)(h2 + 4);
}

template <int N> struct GemmMMA;
template <> struct GemmMMA<64> {
    static __device__ __forceinline__ void run(float* d, uint64_t da, uint64_t db) {
        asm volatile("wgmma.mma_async.sync.aligned.m64n64k16.f32.bf16.bf16 {%0,%1,%2,%3,%4,%5,%6,%7,%8,%9,%10,%11,%12,%13,%14,%15,%16,%17,%18,%19,%20,%21,%22,%23,%24,%25,%26,%27,%28,%29,%30,%31}, %32, %33, 1, 1, 1, 0, 1;"
                     : "+f"(d[0]), "+f"(d[1]), "+f"(d[2]), "+f"(d[3]), "+f"(d[4]), "+f"(d[5]), "+f"(d[6]), "+f"(d[7]), "+f"(d[8]), "+f"(d[9]), "+f"(d[10]), "+f"(d[11]), "+f"(d[12]), "+f"(d[13]), "+f"(d[14]), "+f"(d[15]), "+f"(d[16]), "+f"(d[17]), "+f"(d[18]), "+f"(d[19]), "+f"(d[20]), "+f"(d[21]), "+f"(d[22]), "+f"(d[23]), "+f"(d[24]), "+f"(d[25]), "+f"(d[26]), "+f"(d[27]), "+f"(d[28]), "+f"(d[29]), "+f"(d[30]), "+f"(d[31])
                     : "l"(da), "l"(db));
    }
};
template <> struct GemmMMA<128> {
    static __device__ __forceinline__ void run(float* d, uint64_t da, uint64_t db) {
        asm volatile("wgmma.mma_async.sync.aligned.m64n128k16.f32.bf16.bf16 {%0,%1,%2,%3,%4,%5,%6,%7,%8,%9,%10,%11,%12,%13,%14,%15,%16,%17,%18,%19,%20,%21,%22,%23,%24,%25,%26,%27,%28,%29,%30,%31,%32,%33,%34,%35,%36,%37,%38,%39,%40,%41,%42,%43,%44,%45,%46,%47,%48,%49,%50,%51,%52,%53,%54,%55,%56,%57,%58,%59,%60,%61,%62,%63}, %64, %65, 1, 1, 1, 0, 1;"
                     : "+f"(d[0]), "+f"(d[1]), "+f"(d[2]), "+f"(d[3]), "+f"(d[4]), "+f"(d[5]), "+f"(d[6]), "+f"(d[7]), "+f"(d[8]), "+f"(d[9]), "+f"(d[10]), "+f"(d[11]), "+f"(d[12]), "+f"(d[13]), "+f"(d[14]), "+f"(d[15]), "+f"(d[16]), "+f"(d[17]), "+f"(d[18]), "+f"(d[19]), "+f"(d[20]), "+f"(d[21]), "+f"(d[22]), "+f"(d[23]), "+f"(d[24]), "+f"(d[25]), "+f"(d[26]), "+f"(d[27]), "+f"(d[28]), "+f"(d[29]), "+f"(d[30]), "+f"(d[31]), "+f"(d[32]), "+f"(d[33]), "+f"(d[34]), "+f"(d[35]), "+f"(d[36]), "+f"(d[37]), "+f"(d[38]), "+f"(d[39]), "+f"(d[40]), "+f"(d[41]), "+f"(d[42]), "+f"(d[43]), "+f"(d[44]), "+f"(d[45]), "+f"(d[46]), "+f"(d[47]), "+f"(d[48]), "+f"(d[49]), "+f"(d[50]), "+f"(d[51]), "+f"(d[52]), "+f"(d[53]), "+f"(d[54]), "+f"(d[55]), "+f"(d[56]), "+f"(d[57]), "+f"(d[58]), "+f"(d[59]), "+f"(d[60]), "+f"(d[61]), "+f"(d[62]), "+f"(d[63])
                     : "l"(da), "l"(db));
    }
};
template <> struct GemmMMA<224> {
    static __device__ __forceinline__ void run(float* d, uint64_t da, uint64_t db) {
        asm volatile("wgmma.mma_async.sync.aligned.m64n224k16.f32.bf16.bf16 {%0,%1,%2,%3,%4,%5,%6,%7,%8,%9,%10,%11,%12,%13,%14,%15,%16,%17,%18,%19,%20,%21,%22,%23,%24,%25,%26,%27,%28,%29,%30,%31,%32,%33,%34,%35,%36,%37,%38,%39,%40,%41,%42,%43,%44,%45,%46,%47,%48,%49,%50,%51,%52,%53,%54,%55,%56,%57,%58,%59,%60,%61,%62,%63,%64,%65,%66,%67,%68,%69,%70,%71,%72,%73,%74,%75,%76,%77,%78,%79,%80,%81,%82,%83,%84,%85,%86,%87,%88,%89,%90,%91,%92,%93,%94,%95,%96,%97,%98,%99,%100,%101,%102,%103,%104,%105,%106,%107,%108,%109,%110,%111}, %112, %113, 1, 1, 1, 0, 1;"
                     : "+f"(d[0]), "+f"(d[1]), "+f"(d[2]), "+f"(d[3]), "+f"(d[4]), "+f"(d[5]), "+f"(d[6]), "+f"(d[7]), "+f"(d[8]), "+f"(d[9]), "+f"(d[10]), "+f"(d[11]), "+f"(d[12]), "+f"(d[13]), "+f"(d[14]), "+f"(d[15]), "+f"(d[16]), "+f"(d[17]), "+f"(d[18]), "+f"(d[19]), "+f"(d[20]), "+f"(d[21]), "+f"(d[22]), "+f"(d[23]), "+f"(d[24]), "+f"(d[25]), "+f"(d[26]), "+f"(d[27]), "+f"(d[28]), "+f"(d[29]), "+f"(d[30]), "+f"(d[31]), "+f"(d[32]), "+f"(d[33]), "+f"(d[34]), "+f"(d[35]), "+f"(d[36]), "+f"(d[37]), "+f"(d[38]), "+f"(d[39]), "+f"(d[40]), "+f"(d[41]), "+f"(d[42]), "+f"(d[43]), "+f"(d[44]), "+f"(d[45]), "+f"(d[46]), "+f"(d[47]), "+f"(d[48]), "+f"(d[49]), "+f"(d[50]), "+f"(d[51]), "+f"(d[52]), "+f"(d[53]), "+f"(d[54]), "+f"(d[55]), "+f"(d[56]), "+f"(d[57]), "+f"(d[58]), "+f"(d[59]), "+f"(d[60]), "+f"(d[61]), "+f"(d[62]), "+f"(d[63]), "+f"(d[64]), "+f"(d[65]), "+f"(d[66]), "+f"(d[67]), "+f"(d[68]), "+f"(d[69]), "+f"(d[70]), "+f"(d[71]), "+f"(d[72]), "+f"(d[73]), "+f"(d[74]), "+f"(d[75]), "+f"(d[76]), "+f"(d[77]), "+f"(d[78]), "+f"(d[79]), "+f"(d[80]), "+f"(d[81]), "+f"(d[82]), "+f"(d[83]), "+f"(d[84]), "+f"(d[85]), "+f"(d[86]), "+f"(d[87]), "+f"(d[88]), "+f"(d[89]), "+f"(d[90]), "+f"(d[91]), "+f"(d[92]), "+f"(d[93]), "+f"(d[94]), "+f"(d[95]), "+f"(d[96]), "+f"(d[97]), "+f"(d[98]), "+f"(d[99]), "+f"(d[100]), "+f"(d[101]), "+f"(d[102]), "+f"(d[103]), "+f"(d[104]), "+f"(d[105]), "+f"(d[106]), "+f"(d[107]), "+f"(d[108]), "+f"(d[109]), "+f"(d[110]), "+f"(d[111])
                     : "l"(da), "l"(db));
    }
};
template <> struct GemmMMA<256> {
    static __device__ __forceinline__ void run(float* d, uint64_t da, uint64_t db) {
        asm volatile("wgmma.mma_async.sync.aligned.m64n256k16.f32.bf16.bf16 {%0,%1,%2,%3,%4,%5,%6,%7,%8,%9,%10,%11,%12,%13,%14,%15,%16,%17,%18,%19,%20,%21,%22,%23,%24,%25,%26,%27,%28,%29,%30,%31,%32,%33,%34,%35,%36,%37,%38,%39,%40,%41,%42,%43,%44,%45,%46,%47,%48,%49,%50,%51,%52,%53,%54,%55,%56,%57,%58,%59,%60,%61,%62,%63,%64,%65,%66,%67,%68,%69,%70,%71,%72,%73,%74,%75,%76,%77,%78,%79,%80,%81,%82,%83,%84,%85,%86,%87,%88,%89,%90,%91,%92,%93,%94,%95,%96,%97,%98,%99,%100,%101,%102,%103,%104,%105,%106,%107,%108,%109,%110,%111,%112,%113,%114,%115,%116,%117,%118,%119,%120,%121,%122,%123,%124,%125,%126,%127}, %128, %129, 1, 1, 1, 0, 1;"
                     : "+f"(d[0]), "+f"(d[1]), "+f"(d[2]), "+f"(d[3]), "+f"(d[4]), "+f"(d[5]), "+f"(d[6]), "+f"(d[7]), "+f"(d[8]), "+f"(d[9]), "+f"(d[10]), "+f"(d[11]), "+f"(d[12]), "+f"(d[13]), "+f"(d[14]), "+f"(d[15]), "+f"(d[16]), "+f"(d[17]), "+f"(d[18]), "+f"(d[19]), "+f"(d[20]), "+f"(d[21]), "+f"(d[22]), "+f"(d[23]), "+f"(d[24]), "+f"(d[25]), "+f"(d[26]), "+f"(d[27]), "+f"(d[28]), "+f"(d[29]), "+f"(d[30]), "+f"(d[31]), "+f"(d[32]), "+f"(d[33]), "+f"(d[34]), "+f"(d[35]), "+f"(d[36]), "+f"(d[37]), "+f"(d[38]), "+f"(d[39]), "+f"(d[40]), "+f"(d[41]), "+f"(d[42]), "+f"(d[43]), "+f"(d[44]), "+f"(d[45]), "+f"(d[46]), "+f"(d[47]), "+f"(d[48]), "+f"(d[49]), "+f"(d[50]), "+f"(d[51]), "+f"(d[52]), "+f"(d[53]), "+f"(d[54]), "+f"(d[55]), "+f"(d[56]), "+f"(d[57]), "+f"(d[58]), "+f"(d[59]), "+f"(d[60]), "+f"(d[61]), "+f"(d[62]), "+f"(d[63]), "+f"(d[64]), "+f"(d[65]), "+f"(d[66]), "+f"(d[67]), "+f"(d[68]), "+f"(d[69]), "+f"(d[70]), "+f"(d[71]), "+f"(d[72]), "+f"(d[73]), "+f"(d[74]), "+f"(d[75]), "+f"(d[76]), "+f"(d[77]), "+f"(d[78]), "+f"(d[79]), "+f"(d[80]), "+f"(d[81]), "+f"(d[82]), "+f"(d[83]), "+f"(d[84]), "+f"(d[85]), "+f"(d[86]), "+f"(d[87]), "+f"(d[88]), "+f"(d[89]), "+f"(d[90]), "+f"(d[91]), "+f"(d[92]), "+f"(d[93]), "+f"(d[94]), "+f"(d[95]), "+f"(d[96]), "+f"(d[97]), "+f"(d[98]), "+f"(d[99]), "+f"(d[100]), "+f"(d[101]), "+f"(d[102]), "+f"(d[103]), "+f"(d[104]), "+f"(d[105]), "+f"(d[106]), "+f"(d[107]), "+f"(d[108]), "+f"(d[109]), "+f"(d[110]), "+f"(d[111]), "+f"(d[112]), "+f"(d[113]), "+f"(d[114]), "+f"(d[115]), "+f"(d[116]), "+f"(d[117]), "+f"(d[118]), "+f"(d[119]), "+f"(d[120]), "+f"(d[121]), "+f"(d[122]), "+f"(d[123]), "+f"(d[124]), "+f"(d[125]), "+f"(d[126]), "+f"(d[127])
                     : "l"(da), "l"(db));
    }
};

__device__ __forceinline__ void mbar_init(uint32_t bar, uint32_t cnt) {
    asm volatile("mbarrier.init.shared::cta.b64 [%0], %1;" ::"r"(bar), "r"(cnt) : "memory");
}
__device__ __forceinline__ void mbar_expect_tx(uint32_t bar, uint32_t bytes) {
    asm volatile("mbarrier.arrive.expect_tx.shared::cta.b64 _, [%0], %1;" ::"r"(bar), "r"(bytes) : "memory");
}
__device__ __forceinline__ void mbar_arrive(uint32_t bar) {
    asm volatile("mbarrier.arrive.shared::cta.b64 _, [%0];" ::"r"(bar) : "memory");
}
__device__ __forceinline__ void mbar_wait(uint32_t bar, uint32_t parity) {
    uint32_t done = 0;
    for (int it = 0; it < (1 << 24) && !done; ++it) {
        asm volatile("{\n .reg .pred p;\n mbarrier.try_wait.parity.shared::cta.b64 p, [%1], %2;\n selp.u32 %0, 1, 0, p;\n}"
                     : "=r"(done) : "r"(bar), "r"(parity) : "memory");
    }
}
__device__ __forceinline__ void tma_load_2d(uint32_t dst, const CUtensorMap* tm, int c0, int c1, uint32_t bar) {
    asm volatile("cp.async.bulk.tensor.2d.shared::cluster.global.mbarrier::complete_tx::bytes [%0], [%1, {%3, %4}], [%2];"
                 ::"r"(dst), "l"(tm), "r"(bar), "r"(c0), "r"(c1) : "memory");
}

constexpr int G_STAGES = 4;
template <int BN> struct GemmCfg {
    static constexpr int NB = (BN + 63) / 64;
    static constexpr int A_BYTES = 128 * 64 * 2;
    static constexpr int B_BYTES = NB * 8192;
    static constexpr int STAGE = A_BYTES + B_BYTES;
    static constexpr int SMEM = G_STAGES * STAGE + 1024 + 256;
};

template <int BN, int KT, int MODE>
__global__ void __launch_bounds__(384, 1)
k_gemm_tc(const __grid_constant__ CUtensorMap tmA, const __grid_constant__ CUtensorMap tmB, bf16* __restrict__ out, int ldo) {
    using C = GemmCfg<BN>;
    extern __shared__ uint8_t gsm[];
    const uint32_t sbase = (smem_u32(gsm) + 1023) & ~1023u;
    const uint32_t bars = sbase + G_STAGES * C::STAGE;
    const int tid = threadIdx.x, wg = tid >> 7;
    const int m0 = blockIdx.y * 128, n0 = blockIdx.x * BN;
    if (tid == 0) {
        for (int i = 0; i < G_STAGES; i++) { mbar_init(bars + 8 * i, 1); mbar_init(bars + 32 + 8 * i, 2); }
        asm volatile("fence.mbarrier_init.release.cluster;" ::: "memory");
    }
    __syncthreads();
    if (wg == 2) {
        if (tid == 256) {
            for (int kt = 0; kt < KT; kt++) {
                const int st = kt % G_STAGES;
                if (kt >= G_STAGES) mbar_wait(bars + 32 + 8 * st, ((kt / G_STAGES) - 1) & 1);
                const uint32_t sa = sbase + st * C::STAGE, sb = sa + C::A_BYTES;
                mbar_expect_tx(bars + 8 * st, C::STAGE);
                tma_load_2d(sa, &tmA, kt * 64, m0, bars + 8 * st);
#pragma unroll
                for (int j = 0; j < C::NB; j++) tma_load_2d(sb + j * 8192, &tmB, n0 + 64 * j, kt * 64, bars + 8 * st);
            }
        }
    } else {
        float acc[BN / 2];
#pragma unroll
        for (int i = 0; i < BN / 2; i++) acc[i] = 0.f;
        constexpr uint64_t DA_HI = ((uint64_t)1 << 16) | ((uint64_t)(1024 >> 4) << 32) | ((uint64_t)1 << 62);
        constexpr uint64_t DB_HI = ((uint64_t)(8192 >> 4) << 16) | ((uint64_t)(1024 >> 4) << 32) | ((uint64_t)1 << 62);
#pragma unroll 1
        for (int kt = 0; kt < KT; kt++) {
            const int st = kt % G_STAGES;
            mbar_wait(bars + 8 * st, (kt / G_STAGES) & 1);
            const uint32_t sa = sbase + st * C::STAGE + wg * 8192, sb = sbase + st * C::STAGE + C::A_BYTES;
            const uint64_t da = DA_HI | (uint64_t)((sa & 0x3FFFF) >> 4);
            const uint64_t db = DB_HI | (uint64_t)((sb & 0x3FFFF) >> 4);
            wg_fence();
#pragma unroll
            for (int k = 0; k < 4; k++) GemmMMA<BN>::run(acc, da + 2 * k, db + 128 * k);
            wg_commit();
            wg_wait<1>();
            if (kt > 0 && (tid & 127) == 0) mbar_arrive(bars + 32 + 8 * ((kt - 1) % G_STAGES));
        }
        wg_wait<0>();
        asm volatile("bar.sync 1, 256;" ::: "memory");
        const int lane = tid & 31, w = (tid >> 5) & 3, g = lane >> 2, t = lane & 3;
        constexpr int PITCH = BN * 2 + 16;
        uint8_t* stg = gsm + (sbase - smem_u32(gsm));
#pragma unroll
        for (int h = 0; h < 2; h++) {
            const int row = wg * 64 + w * 16 + g + 8 * h;
#pragma unroll
            for (int j = 0; j < BN / 8; j++) {
                float v0 = acc[4 * j + 2 * h], v1 = acc[4 * j + 2 * h + 1];
                bf162 o;
                if (MODE == 0) {
                    float h0 = bfr(v0), h1 = bfr(v1);
                    o = __floats2bfloat162_rn(__fdividef(h0, 1.f + __expf(-h0)), __fdividef(h1, 1.f + __expf(-h1)));
                } else {
                    o = __floats2bfloat162_rn(v0, v1);
                }
                *(bf162*)(stg + row * PITCH + (8 * j + 2 * t) * 2) = o;
            }
        }
        asm volatile("bar.sync 1, 256;" ::: "memory");
        constexpr int CPR = BN / 8;
#pragma unroll 2
        for (int idx = tid; idx < 128 * CPR; idx += 256) {
            const int row = idx / CPR, ck = idx % CPR;
            uint4 vv = *(const uint4*)(stg + row * PITCH + ck * 16);
            bf16* dst = out + (size_t)(m0 + row) * ldo + n0 + ck * 8;
            if (MODE == 1) {
                uint4 xv = *(const uint4*)(g_x1 + (size_t)(m0 + row) * D_DIM + n0 + ck * 8);
                const float4* gp = (const float4*)(g_mod + 5 * D_DIM + n0 + ck * 8);
                float4 g0 = gp[0], g1 = gp[1];
                float gbv[8] = {g0.x, g0.y, g0.z, g0.w, g1.x, g1.y, g1.z, g1.w};
                const bf16* po = (const bf16*)&vv;
                const bf16* px = (const bf16*)&xv;
                uint4 r;
                bf16* pr = (bf16*)&r;
#pragma unroll
                for (int e = 0; e < 8; e++) pr[e] = __float2bfloat16_rn(b2f(px[e]) + bfr(gbv[e] * b2f(po[e])));
                vv = r;
            }
            *(uint4*)dst = vv;
        }
    }
}

typedef CUresult (*PFN_encodeTiled)(CUtensorMap*, CUtensorMapDataType, cuuint32_t, void*, const cuuint64_t*, const cuuint64_t*,
                                    const cuuint32_t*, const cuuint32_t*, CUtensorMapInterleave, CUtensorMapSwizzle,
                                    CUtensorMapL2promotion, CUtensorMapFloatOOBfill);

static void make_map(PFN_encodeTiled enc, CUtensorMap* m, const void* ptr, uint64_t inner, uint64_t outer, uint32_t boxi, uint32_t boxo) {
    cuuint64_t dims[2] = {inner, outer};
    cuuint64_t strides[1] = {inner * 2};
    cuuint32_t box[2] = {boxi, boxo};
    cuuint32_t es[2] = {1, 1};
    enc(m, CU_TENSOR_MAP_DATA_TYPE_BFLOAT16, 2, (void*)ptr, dims, strides, box, es, CU_TENSOR_MAP_INTERLEAVE_NONE,
        CU_TENSOR_MAP_SWIZZLE_128B, CU_TENSOR_MAP_L2_PROMOTION_L2_128B, CU_TENSOR_MAP_FLOAT_OOB_FILL_NONE);
}

extern "C" void kernel_launch(void* const* d_in, const int* in_sizes, int n_in,
                              void* d_out, int out_size) {
    const bf16* q = (const bf16*)d_in[0];
    const bf16* k = (const bf16*)d_in[1];
    const bf16* v = (const bf16*)d_in[2];
    const bf16* shift_k = (const bf16*)d_in[3];
    const bf16* ssm_k = (const bf16*)d_in[4];
    const bf16* ssm_D = (const bf16*)d_in[5];
    const bf16* w1 = (const bf16*)d_in[7];
    const bf16* w2 = (const bf16*)d_in[8];
    const bf16* c = (const bf16*)d_in[9];
    const bf16* w_mod = (const bf16*)d_in[10];
    bf16* out = (bf16*)d_out;

    static bool init = false;
    static CUtensorMap tm_h2, tm_w1, tm_h1, tm_w2;
    static bf16 *h2p, *h1p;
    if (!init) {
        cudaFuncSetAttribute(k_conv, cudaFuncAttributeMaxDynamicSharedMemorySize, CONV_SMEM);
        cudaFuncSetAttribute(k_gemm_tc<224, 8, 0>, cudaFuncAttributeMaxDynamicSharedMemorySize, GemmCfg<224>::SMEM);
        cudaFuncSetAttribute(k_gemm_tc<64, 28, 1>, cudaFuncAttributeMaxDynamicSharedMemorySize, GemmCfg<64>::SMEM);
        cudaGetSymbolAddress((void**)&h2p, g_h2);
        cudaGetSymbolAddress((void**)&h1p, g_h1);
        PFN_encodeTiled enc = nullptr;
        cudaDriverEntryPointQueryResult qr;
        cudaGetDriverEntryPoint("cuTensorMapEncodeTiled", (void**)&enc, cudaEnableDefault, &qr);
        make_map(enc, &tm_h2, h2p, D_DIM, S_LEN, 64, 128);
        make_map(enc, &tm_w1, w1, F_DIM, D_DIM, 64, 64);
        make_map(enc, &tm_h1, h1p, F_DIM, S_LEN, 64, 128);
        make_map(enc, &tm_w2, w2, D_DIM, F_DIM, 64, 64);
        init = true;
    }
    k_conv<<<D_DIM / 4, CONV_THREADS, CONV_SMEM>>>(k, v, shift_k, ssm_k, ssm_D, c, w_mod);
    k_mid<<<S_LEN / MID_ROWS, 512>>>(q);
    k_gemm_tc<224, 8, 0><<<dim3(F_DIM / 224, S_LEN / 128), 384, GemmCfg<224>::SMEM>>>(tm_h2, tm_w1, h1p, F_DIM);
    k_gemm_tc<64, 28, 1><<<dim3(D_DIM / 64, S_LEN / 128), 384, GemmCfg<64>::SMEM>>>(tm_h1, tm_w2, out, D_DIM);
}
```

```cpp
#include <cuda_runtime.h>
#include <cuda.h>
#include <cuda_bf16.h>
#include <stdint.h>

#define S_LEN 2048
#define D_DIM 512
#define F_DIM 1792

typedef __nv_bfloat16 bf16;
typedef __nv_bfloat162 bf162;

__device__ float g_mod[6 * D_DIM];
__device__ bf16 g_y2T[D_DIM * S_LEN];
__device__ bf16 g_x1[S_LEN * D_DIM];
__device__ bf16 g_h2[S_LEN * D_DIM];
__device__ bf16 g_h1[S_LEN * F_DIM];

__device__ __forceinline__ float bfr(float x) { return __bfloat162float(__float2bfloat16_rn(x)); }
__device__ __forceinline__ float b2f(bf16 x) { return __bfloat162float(x); }
__device__ __forceinline__ uint32_t smem_u32(const void* p) { return (uint32_t)__cvta_generic_to_shared(p); }

constexpr int CONV_THREADS = 512;
constexpr int R_WORDS = 1064;
constexpr int R_BYTES = 2 * R_WORDS * 4;
constexpr int U_CHUNK = 656;
constexpr int U_BYTES = 8 * U_CHUNK;
constexpr int CH_BYTES = R_BYTES + U_BYTES;
constexpr int CONV_SMEM = 4 * CH_BYTES + 16 * 24 * 4;

__device__ __forceinline__ void wg_fence() { asm volatile("wgmma.fence.sync.aligned;" ::: "memory"); }
__device__ __forceinline__ void wg_commit() { asm volatile("wgmma.commit_group.sync.aligned;" ::: "memory"); }
template <int N> __device__ __forceinline__ void wg_wait() { asm volatile("wgmma.wait_group.sync.aligned %0;" ::"n"(N) : "memory"); }

template <int NT> struct ConvMMA;
template <> struct ConvMMA<1> {
    static __device__ __forceinline__ void run(float* d, uint32_t a0, uint32_t a1, uint32_t a2, uint32_t a3, uint64_t desc) {
        asm volatile("wgmma.mma_async.sync.aligned.m64n8k16.f32.bf16.bf16 {%0,%1,%2,%3}, {%4,%5,%6,%7}, %8, 1, 1, 1, 0;"
                     : "+f"(d[12]), "+f"(d[13]), "+f"(d[14]), "+f"(d[15])
                     : "r"(a0), "r"(a1), "r"(a2), "r"(a3), "l"(desc));
    }
};
template <> struct ConvMMA<2> {
    static __device__ __forceinline__ void run(float* d, uint32_t a0, uint32_t a1, uint32_t a2, uint32_t a3, uint64_t desc) {
        asm volatile("wgmma.mma_async.sync.aligned.m64n16k16.f32.bf16.bf16 {%0,%1,%2,%3,%4,%5,%6,%7}, {%8,%9,%10,%11}, %12, 1, 1, 1, 0;"
                     : "+f"(d[8]), "+f"(d[9]), "+f"(d[10]), "+f"(d[11]), "+f"(d[12]), "+f"(d[13]), "+f"(d[14]), "+f"(d[15])
                     : "r"(a0), "r"(a1), "r"(a2), "r"(a3), "l"(desc));
    }
};
template <> struct ConvMMA<3> {
    static __device__ __forceinline__ void run(float* d, uint32_t a0, uint32_t a1, uint32_t a2, uint32_t a3, uint64_t desc) {
        asm volatile("wgmma.mma_async.sync.aligned.m64n24k16.f32.bf16.bf16 {%0,%1,%2,%3,%4,%5,%6,%7,%8,%9,%10,%11}, {%12,%13,%14,%15}, %16, 1, 1, 1, 0;"
                     : "+f"(d[4]), "+f"(d[5]), "+f"(d[6]), "+f"(d[7]), "+f"(d[8]), "+f"(d[9]), "+f"(d[10]), "+f"(d[11]),
                       "+f"(d[12]), "+f"(d[13]), "+f"(d[14]), "+f"(d[15])
                     : "r"(a0), "r"(a1), "r"(a2), "r"(a3), "l"(desc));
    }
};
template <> struct ConvMMA<4> {
    static __device__ __forceinline__ void run(float* d, uint32_t a0, uint32_t a1, uint32_t a2, uint32_t a3, uint64_t desc) {
        asm volatile("wgmma.mma_async.sync.aligned.m64n32k16.f32.bf16.bf16 {%0,%1,%2,%3,%4,%5,%6,%7,%8,%9,%10,%11,%12,%13,%14,%15}, {%16,%17,%18,%19}, %20, 1, 1, 1, 0;"
                     : "+f"(d[0]), "+f"(d[1]), "+f"(d[2]), "+f"(d[3]), "+f"(d[4]), "+f"(d[5]), "+f"(d[6]), "+f"(d[7]),
                       "+f"(d[8]), "+f"(d[9]), "+f"(d[10]), "+f"(d[11]), "+f"(d[12]), "+f"(d[13]), "+f"(d[14]), "+f"(d[15])
                     : "r"(a0), "r"(a1), "r"(a2), "r"(a3), "l"(desc));
    }
};

__device__ __forceinline__ uint32_t lds32(uint32_t addr) {
    uint32_t v;
    asm volatile("ld.shared.u32 %0, [%1];" : "=r"(v) : "r"(addr));
    return v;
}

template <int NT>
__device__ __forceinline__ void conv_group(float* d, uint32_t rbase, uint32_t ubase, uint32_t* wA) {
    constexpr int A_LO = 8 * (4 - NT);
    constexpr uint64_t DESC_HI = ((uint64_t)(U_CHUNK >> 4) << 16) | ((uint64_t)(128 >> 4) << 32);
#pragma unroll 1
    for (int c = A_LO + 7; c >= A_LO; c -= 2) {
        uint32_t wB[9];
        uint32_t ub = ubase + (7 + A_LO - c) * 16;
        uint64_t da = DESC_HI | (uint64_t)((ub & 0x3FFFF) >> 4);
        wg_fence();
#pragma unroll
        for (int js = 0; js < 4; js++)
            ConvMMA<NT>::run(d, wA[2 * js + 1], wA[2 * js], wA[2 * js + 2], wA[2 * js + 1], da + (uint64_t)((2 * js * U_CHUNK) >> 4));
        wg_commit();
        {
            uint32_t ra = rbase - 128 * (c - 1) - 16;
#pragma unroll
            for (int m = 0; m < 9; m++) wB[m] = lds32(ra + 16 * m);
        }
        wg_fence();
#pragma unroll
        for (int js = 0; js < 4; js++)
            ConvMMA<NT>::run(d, wB[2 * js + 1], wB[2 * js], wB[2 * js + 2], wB[2 * js + 1], da + (uint64_t)((2 * js * U_CHUNK + 16) >> 4));
        wg_commit();
        wg_wait<1>();
        {
            uint32_t ra = rbase - 128 * (c - 2) - 16;
#pragma unroll
            for (int m = 0; m < 9; m++) wA[m] = lds32(ra + 16 * m);
        }
    }
    wg_wait<0>();
}

__global__ void __launch_bounds__(CONV_THREADS, 1)
k_conv(const bf16* __restrict__ k, const bf16* __restrict__ v, const bf16* __restrict__ shift_k,
       const bf16* __restrict__ ssm_k, const bf16* __restrict__ ssm_D,
       const bf16* __restrict__ cvec, const bf16* __restrict__ w_mod) {
    extern __shared__ __align__(128) uint8_t smem[];
    const int tid = threadIdx.x;

    const int d0 = blockIdx.x * 4;
    float* modred = (float*)(smem + 4 * CH_BYTES);
    const uint4* wmp = (const uint4*)(w_mod + (size_t)tid * (6 * D_DIM) + blockIdx.x * 24);
    uint4 wm0 = wmp[0], wm1 = wmp[1], wm2 = wmp[2];
    const float cvi = b2f(cvec[tid]);

    if (tid < 256) {
        const int s0 = tid * 8;
        uint2 kr[11], vr[8];
#pragma unroll
        for (int r = 0; r < 11; r++) {
            int s = s0 - 3 + r;
            kr[r] = s >= 0 ? *(const uint2*)(k + (size_t)s * D_DIM + d0) : make_uint2(0u, 0u);
        }
#pragma unroll
        for (int r = 0; r < 8; r++) vr[r] = *(const uint2*)(v + (size_t)(s0 + r) * D_DIM + d0);
        uint4 sk0 = *(const uint4*)(shift_k + d0 * 4);
        uint4 sk1 = *(const uint4*)(shift_k + d0 * 4 + 8);
        uint32_t tp[4][2];
        tp[0][0] = __byte_perm(sk0.x, sk0.z, 0x5410); tp[1][0] = __byte_perm(sk0.x, sk0.z, 0x7632);
        tp[2][0] = __byte_perm(sk0.y, sk0.w, 0x5410); tp[3][0] = __byte_perm(sk0.y, sk0.w, 0x7632);
        tp[0][1] = __byte_perm(sk1.x, sk1.z, 0x5410); tp[1][1] = __byte_perm(sk1.x, sk1.z, 0x7632);
        tp[2][1] = __byte_perm(sk1.y, sk1.w, 0x5410); tp[3][1] = __byte_perm(sk1.y, sk1.w, 0x7632);
        uint32_t kvp[8][2];
#pragma unroll
        for (int r = 0; r < 8; r++) {
#pragma unroll
            for (int h = 0; h < 2; h++) {
                auto K = [&](int rr) { uint32_t u = h ? kr[rr].y : kr[rr].x; return *(bf162*)&u; };
                auto T = [&](int j) { uint32_t u = tp[j][h]; return *(bf162*)&u; };
                uint32_t vv = h ? vr[r].y : vr[r].x;
                bf162 acc = __hmul2_rn(K(r), T(3));
                acc = __hadd2_rn(acc, __hmul2_rn(K(r + 1), T(2)));
                acc = __hadd2_rn(acc, __hmul2_rn(K(r + 2), T(1)));
                acc = __hadd2_rn(acc, __hmul2_rn(K(r + 3), T(0)));
                bf162 kvv = __hmul2_rn(acc, *(bf162*)&vv);
                kvp[r][h] = *(uint32_t*)&kvv;
            }
        }
        const int b = tid >> 3, jc = tid & 7;
#pragma unroll
        for (int ch = 0; ch < 4; ch++) {
            const int h = ch >> 1;
            const uint32_t sel = (ch & 1) ? 0x7632 : 0x5410;
            uint4 o;
            o.x = __byte_perm(kvp[0][h], kvp[1][h], sel);
            o.y = __byte_perm(kvp[2][h], kvp[3][h], sel);
            o.z = __byte_perm(kvp[4][h], kvp[5][h], sel);
            o.w = __byte_perm(kvp[6][h], kvp[7][h], sel);
            *(uint4*)(smem + ch * CH_BYTES + R_BYTES + jc * U_CHUNK + (7 + b) * 16) = o;
        }
    } else {
        const int t2 = tid - 256;
#pragma unroll
        for (int ch = 0; ch < 4; ch++) {
            const bf16* kk = ssm_k + (size_t)(d0 + ch) * S_LEN;
            const int G = t2;
            uint4 a = *(const uint4*)(kk + 8 * G);
            uint32_t pw = G > 0 ? ((uint32_t)(*(const uint16_t*)(kk + 8 * G - 1)) << 16) : 0u;
            uint4 c1, c0;
            c1.x = __byte_perm(a.w, 0, 0x1032); c1.y = __byte_perm(a.z, 0, 0x1032);
            c1.z = __byte_perm(a.y, 0, 0x1032); c1.w = __byte_perm(a.x, 0, 0x1032);
            c0.x = __byte_perm(a.w, a.z, 0x7610); c0.y = __byte_perm(a.z, a.y, 0x7610);
            c0.z = __byte_perm(a.y, a.x, 0x7610); c0.w = __byte_perm(a.x, pw, 0x7610);
            uint8_t* R = smem + ch * CH_BYTES;
            *(uint4*)(R + (1020 - 4 * G) * 4) = c0;
            *(uint4*)(R + R_WORDS * 4 + (1020 - 4 * G) * 4) = c1;
        }
        if (t2 < 80) {
            int ch = t2 / 20, r = t2 % 20;
            uint8_t* R = smem + ch * CH_BYTES;
            *(uint4*)(R + (r / 10) * R_WORDS * 4 + (1024 + 4 * (r % 10)) * 4) = make_uint4(0, 0, 0, 0);
        } else if (t2 < 80 + 4 * 8 * 7 && t2 >= 80) {
        }
        for (int i = t2; i < 4 * 8 * 7; i += 256) {
            int ch = i / 56, r = i % 56, jc = r / 7, row = r % 7;
            *(uint4*)(smem + ch * CH_BYTES + R_BYTES + jc * U_CHUNK + row * 16) = make_uint4(0, 0, 0, 0);
        }
    }
    asm volatile("fence.proxy.async.shared::cta;" ::: "memory");
    __syncthreads();

    const int wg = tid >> 7, w = (tid >> 5) & 3, lane = tid & 31, g = lane >> 2, t = lane & 3;
    const uint32_t chb = smem_u32(smem) + wg * CH_BYTES;
    const uint32_t rbase = chb + (g & 1) * (R_WORDS * 4) + 4 * (1023 - 8 * w - (g >> 1) + t);
    const uint32_t ubase = chb + R_BYTES;
    float d[16], d1[16], d2[16], d3[16];
#pragma unroll
    for (int i = 0; i < 16; i++) { d[i] = 0.f; d1[i] = 0.f; d2[i] = 0.f; d3[i] = 0.f; }
    uint32_t wv[9];
#pragma unroll
    for (int m = 0; m < 9; m++) wv[m] = lds32(rbase - 128 * 31 - 16 + 16 * m);
    conv_group<1>(d1, rbase, ubase, wv);
    conv_group<2>(d2, rbase, ubase, wv);
    conv_group<3>(d3, rbase, ubase, wv);
    conv_group<4>(d, rbase, ubase, wv);
#pragma unroll
    for (int i = 12; i < 16; i++) d[i] += d1[i];
#pragma unroll
    for (int i = 8; i < 16; i++) d[i] += d2[i];
#pragma unroll
    for (int i = 4; i < 16; i++) d[i] += d3[i];

    const int dch = d0 + wg;
    const float Dv = b2f(ssm_D[dch]);
    bf16* yo = g_y2T + (size_t)dch * S_LEN;
    const uint8_t* U = smem + wg * CH_BYTES + R_BYTES;
#pragma unroll
    for (int nt = 0; nt < 4; nt++) {
#pragma unroll
        for (int e = 0; e < 4; e++) {
            int i = 16 * w + g + (e >> 1) * 8;
            int a = 8 * nt + 2 * t + (e & 1);
            float u = b2f(*(const bf16*)(U + (i >> 3) * U_CHUNK + (7 + a) * 16 + (i & 7) * 2));
            float y = bfr(d[4 * nt + e]);
            y = y + bfr(u * Dv);
            yo[64 * a + i] = __float2bfloat16_rn(y);
        }
    }
    {
        const float sl = bfr(cvi / (1.f + __expf(-cvi)));
        uint32_t ww[12] = {wm0.x, wm0.y, wm0.z, wm0.w, wm1.x, wm1.y, wm1.z, wm1.w, wm2.x, wm2.y, wm2.z, wm2.w};
        float acc[24];
#pragma unroll
        for (int e = 0; e < 12; e++) {
            acc[2 * e] = sl * __uint_as_float(ww[e] << 16);
            acc[2 * e + 1] = sl * __uint_as_float(ww[e] & 0xffff0000u);
        }
#pragma unroll
        for (int j = 0; j < 24; j++) {
#pragma unroll
            for (int o = 16; o > 0; o >>= 1) acc[j] += __shfl_xor_sync(0xffffffffu, acc[j], o);
        }
        if ((tid & 31) == 0) {
#pragma unroll
            for (int j = 0; j < 24; j++) modred[(tid >> 5) * 24 + j] = acc[j];
        }
        __syncthreads();
        if (tid < 24) {
            float sum = 0.f;
#pragma unroll
            for (int wq = 0; wq < 16; wq++) sum += modred[wq * 24 + tid];
            g_mod[blockIdx.x * 24 + tid] = bfr(sum);
        }
    }
}

constexpr int MID_ROWS = 16;
__device__ __forceinline__ bf162 u2b(uint32_t u) { return *(bf162*)&u; }
__device__ __forceinline__ uint32_t b2u(bf162 b) { return *(uint32_t*)&b; }
__device__ __forceinline__ void row_stats(const uint32_t* xp, bf162& m2, float& rden) {
    float sum = 0.f;
#pragma unroll
    for (int i = 0; i < 8; i++) { float2 f = __bfloat1622float2(u2b(xp[i])); sum += f.x + f.y; }
#pragma unroll
    for (int o = 16; o > 0; o >>= 1) sum += __shfl_xor_sync(0xffffffffu, sum, o);
    const float mean = sum * (1.f / D_DIM);
    float sq = 0.f;
#pragma unroll
    for (int i = 0; i < 8; i++) { float2 f = __bfloat1622float2(u2b(xp[i])); sq += (f.x - mean) * (f.x - mean) + (f.y - mean) * (f.y - mean); }
#pragma unroll
    for (int o = 16; o > 0; o >>= 1) sq += __shfl_xor_sync(0xffffffffu, sq, o);
    const bf16 mb = __float2bfloat16_rn(mean);
    m2 = __halves2bfloat162(mb, mb);
    const float den = bfr(sqrtf(bfr(bfr(sq * (1.f / D_DIM)) + 1e-5f)));
    rden = 1.f / den;
}
__global__ void __launch_bounds__(512, 2) k_mid(const bf16* __restrict__ x) {
    __shared__ __align__(16) bf16 ys[MID_ROWS][D_DIM + 8];
    const int tid = threadIdx.x, lane = tid & 31, wid = tid >> 5;
    const int s0 = blockIdx.x * MID_ROWS;
    asm volatile("griddepcontrol.wait;" ::: "memory");

    {
        const uint4* p = (const uint4*)(g_y2T + (size_t)tid * S_LEN + s0);
        uint4 a = p[0], b = p[1];
        const bf16* pa = (const bf16*)&a;
        const bf16* pb = (const bf16*)&b;
#pragma unroll
        for (int r = 0; r < 8; r++) { ys[r][tid] = pa[r]; ys[r + 8][tid] = pb[r]; }
    }
    const int s = s0 + wid;
    uint32_t xp[8];
    *(uint4*)xp = *(const uint4*)(x + (size_t)s * D_DIM + lane * 8);
    *(uint4*)(xp + 4) = *(const uint4*)(x + (size_t)s * D_DIM + 256 + lane * 8);
    uint32_t c1a[8], csa[8], cga[8], c1b[8], csb[8];
#pragma unroll
    for (int h = 0; h < 2; h++) {
#pragma unroll
        for (int q = 0; q < 4; q++) {
            const int d = h * 256 + lane * 8 + 2 * q;
            float2 sa = *(const float2*)(g_mod + d), ca = *(const float2*)(g_mod + D_DIM + d), ga = *(const float2*)(g_mod + 2 * D_DIM + d);
            float2 sb = *(const float2*)(g_mod + 3 * D_DIM + d), cb = *(const float2*)(g_mod + 4 * D_DIM + d);
            c1a[h * 4 + q] = b2u(__floats2bfloat162_rn(1.f + ca.x, 1.f + ca.y));
            csa[h * 4 + q] = b2u(__floats2bfloat162_rn(sa.x, sa.y));
            cga[h * 4 + q] = b2u(__floats2bfloat162_rn(ga.x, ga.y));
            c1b[h * 4 + q] = b2u(__floats2bfloat162_rn(1.f + cb.x, 1.f + cb.y));
            csb[h * 4 + q] = b2u(__floats2bfloat162_rn(sb.x, sb.y));
        }
    }
    bf162 m2; float rden;
    row_stats(xp, m2, rden);
    __syncthreads();
    uint32_t x1[8];
#pragma unroll
    for (int i = 0; i < 8; i++) {
        const int h = i >> 2, q = i & 3;
        uint32_t yv = *(const uint32_t*)(&ys[wid][h * 256 + lane * 8 + 2 * q]);
        bf162 xm = __hsub2_rn(u2b(xp[i]), m2);
        float2 f = __bfloat1622float2(xm);
        bf162 ln = __floats2bfloat162_rn(f.x * rden, f.y * rden);
        bf162 hh = __hadd2_rn(__hmul2_rn(ln, u2b(c1a[i])), u2b(csa[i]));
        bf162 a = __hmul2_rn(hh, u2b(yv));
        bf162 r = __hadd2_rn(u2b(xp[i]), __hmul2_rn(u2b(cga[i]), a));
        x1[i] = b2u(r);
    }
    *(uint4*)(g_x1 + (size_t)s * D_DIM + lane * 8) = *(uint4*)x1;
    *(uint4*)(g_x1 + (size_t)s * D_DIM + 256 + lane * 8) = *(uint4*)(x1 + 4);
    row_stats(x1, m2, rden);
    uint32_t h2[8];
#pragma unroll
    for (int i = 0; i < 8; i++) {
        bf162 xm = __hsub2_rn(u2b(x1[i]), m2);
        float2 f = __bfloat1622float2(xm);
        bf162 ln = __floats2bfloat162_rn(f.x * rden, f.y * rden);
        h2[i] = b2u(__hadd2_rn(__hmul2_rn(ln, u2b(c1b[i])), u2b(csb[i])));
    }
    *(uint4*)(g_h2 + (size_t)s * D_DIM + lane * 8) = *(uint4*)h2;
    *(uint4*)(g_h2 + (size_t)s * D_DIM + 256 + lane * 8) = *(uint4*)(h2 + 4);
}

template <int N> struct GemmMMA;
template <> struct GemmMMA<64> {
    static __device__ __forceinline__ void run(float* d, uint64_t da, uint64_t db) {
        asm volatile("wgmma.mma_async.sync.aligned.m64n64k16.f32.bf16.bf16 {%0,%1,%2,%3,%4,%5,%6,%7,%8,%9,%10,%11,%12,%13,%14,%15,%16,%17,%18,%19,%20,%21,%22,%23,%24,%25,%26,%27,%28,%29,%30,%31}, %32, %33, 1, 1, 1, 0, 1;"
                     : "+f"(d[0]), "+f"(d[1]), "+f"(d[2]), "+f"(d[3]), "+f"(d[4]), "+f"(d[5]), "+f"(d[6]), "+f"(d[7]), "+f"(d[8]), "+f"(d[9]), "+f"(d[10]), "+f"(d[11]), "+f"(d[12]), "+f"(d[13]), "+f"(d[14]), "+f"(d[15]), "+f"(d[16]), "+f"(d[17]), "+f"(d[18]), "+f"(d[19]), "+f"(d[20]), "+f"(d[21]), "+f"(d[22]), "+f"(d[23]), "+f"(d[24]), "+f"(d[25]), "+f"(d[26]), "+f"(d[27]), "+f"(d[28]), "+f"(d[29]), "+f"(d[30]), "+f"(d[31])
                     : "l"(da), "l"(db));
    }
};
template <> struct GemmMMA<128> {
    static __device__ __forceinline__ void run(float* d, uint64_t da, uint64_t db) {
        asm volatile("wgmma.mma_async.sync.aligned.m64n128k16.f32.bf16.bf16 {%0,%1,%2,%3,%4,%5,%6,%7,%8,%9,%10,%11,%12,%13,%14,%15,%16,%17,%18,%19,%20,%21,%22,%23,%24,%25,%26,%27,%28,%29,%30,%31,%32,%33,%34,%35,%36,%37,%38,%39,%40,%41,%42,%43,%44,%45,%46,%47,%48,%49,%50,%51,%52,%53,%54,%55,%56,%57,%58,%59,%60,%61,%62,%63}, %64, %65, 1, 1, 1, 0, 1;"
                     : "+f"(d[0]), "+f"(d[1]), "+f"(d[2]), "+f"(d[3]), "+f"(d[4]), "+f"(d[5]), "+f"(d[6]), "+f"(d[7]), "+f"(d[8]), "+f"(d[9]), "+f"(d[10]), "+f"(d[11]), "+f"(d[12]), "+f"(d[13]), "+f"(d[14]), "+f"(d[15]), "+f"(d[16]), "+f"(d[17]), "+f"(d[18]), "+f"(d[19]), "+f"(d[20]), "+f"(d[21]), "+f"(d[22]), "+f"(d[23]), "+f"(d[24]), "+f"(d[25]), "+f"(d[26]), "+f"(d[27]), "+f"(d[28]), "+f"(d[29]), "+f"(d[30]), "+f"(d[31]), "+f"(d[32]), "+f"(d[33]), "+f"(d[34]), "+f"(d[35]), "+f"(d[36]), "+f"(d[37]), "+f"(d[38]), "+f"(d[39]), "+f"(d[40]), "+f"(d[41]), "+f"(d[42]), "+f"(d[43]), "+f"(d[44]), "+f"(d[45]), "+f"(d[46]), "+f"(d[47]), "+f"(d[48]), "+f"(d[49]), "+f"(d[50]), "+f"(d[51]), "+f"(d[52]), "+f"(d[53]), "+f"(d[54]), "+f"(d[55]), "+f"(d[56]), "+f"(d[57]), "+f"(d[58]), "+f"(d[59]), "+f"(d[60]), "+f"(d[61]), "+f"(d[62]), "+f"(d[63])
                     : "l"(da), "l"(db));
    }
};
template <> struct GemmMMA<224> {
    static __device__ __forceinline__ void run(float* d, uint64_t da, uint64_t db) {
        asm volatile("wgmma.mma_async.sync.aligned.m64n224k16.f32.bf16.bf16 {%0,%1,%2,%3,%4,%5,%6,%7,%8,%9,%10,%11,%12,%13,%14,%15,%16,%17,%18,%19,%20,%21,%22,%23,%24,%25,%26,%27,%28,%29,%30,%31,%32,%33,%34,%35,%36,%37,%38,%39,%40,%41,%42,%43,%44,%45,%46,%47,%48,%49,%50,%51,%52,%53,%54,%55,%56,%57,%58,%59,%60,%61,%62,%63,%64,%65,%66,%67,%68,%69,%70,%71,%72,%73,%74,%75,%76,%77,%78,%79,%80,%81,%82,%83,%84,%85,%86,%87,%88,%89,%90,%91,%92,%93,%94,%95,%96,%97,%98,%99,%100,%101,%102,%103,%104,%105,%106,%107,%108,%109,%110,%111}, %112, %113, 1, 1, 1, 0, 1;"
                     : "+f"(d[0]), "+f"(d[1]), "+f"(d[2]), "+f"(d[3]), "+f"(d[4]), "+f"(d[5]), "+f"(d[6]), "+f"(d[7]), "+f"(d[8]), "+f"(d[9]), "+f"(d[10]), "+f"(d[11]), "+f"(d[12]), "+f"(d[13]), "+f"(d[14]), "+f"(d[15]), "+f"(d[16]), "+f"(d[17]), "+f"(d[18]), "+f"(d[19]), "+f"(d[20]), "+f"(d[21]), "+f"(d[22]), "+f"(d[23]), "+f"(d[24]), "+f"(d[25]), "+f"(d[26]), "+f"(d[27]), "+f"(d[28]), "+f"(d[29]), "+f"(d[30]), "+f"(d[31]), "+f"(d[32]), "+f"(d[33]), "+f"(d[34]), "+f"(d[35]), "+f"(d[36]), "+f"(d[37]), "+f"(d[38]), "+f"(d[39]), "+f"(d[40]), "+f"(d[41]), "+f"(d[42]), "+f"(d[43]), "+f"(d[44]), "+f"(d[45]), "+f"(d[46]), "+f"(d[47]), "+f"(d[48]), "+f"(d[49]), "+f"(d[50]), "+f"(d[51]), "+f"(d[52]), "+f"(d[53]), "+f"(d[54]), "+f"(d[55]), "+f"(d[56]), "+f"(d[57]), "+f"(d[58]), "+f"(d[59]), "+f"(d[60]), "+f"(d[61]), "+f"(d[62]), "+f"(d[63]), "+f"(d[64]), "+f"(d[65]), "+f"(d[66]), "+f"(d[67]), "+f"(d[68]), "+f"(d[69]), "+f"(d[70]), "+f"(d[71]), "+f"(d[72]), "+f"(d[73]), "+f"(d[74]), "+f"(d[75]), "+f"(d[76]), "+f"(d[77]), "+f"(d[78]), "+f"(d[79]), "+f"(d[80]), "+f"(d[81]), "+f"(d[82]), "+f"(d[83]), "+f"(d[84]), "+f"(d[85]), "+f"(d[86]), "+f"(d[87]), "+f"(d[88]), "+f"(d[89]), "+f"(d[90]), "+f"(d[91]), "+f"(d[92]), "+f"(d[93]), "+f"(d[94]), "+f"(d[95]), "+f"(d[96]), "+f"(d[97]), "+f"(d[98]), "+f"(d[99]), "+f"(d[100]), "+f"(d[101]), "+f"(d[102]), "+f"(d[103]), "+f"(d[104]), "+f"(d[105]), "+f"(d[106]), "+f"(d[107]), "+f"(d[108]), "+f"(d[109]), "+f"(d[110]), "+f"(d[111])
                     : "l"(da), "l"(db));
    }
};
template <> struct GemmMMA<256> {
    static __device__ __forceinline__ void run(float* d, uint64_t da, uint64_t db) {
        asm volatile("wgmma.mma_async.sync.aligned.m64n256k16.f32.bf16.bf16 {%0,%1,%2,%3,%4,%5,%6,%7,%8,%9,%10,%11,%12,%13,%14,%15,%16,%17,%18,%19,%20,%21,%22,%23,%24,%25,%26,%27,%28,%29,%30,%31,%32,%33,%34,%35,%36,%37,%38,%39,%40,%41,%42,%43,%44,%45,%46,%47,%48,%49,%50,%51,%52,%53,%54,%55,%56,%57,%58,%59,%60,%61,%62,%63,%64,%65,%66,%67,%68,%69,%70,%71,%72,%73,%74,%75,%76,%77,%78,%79,%80,%81,%82,%83,%84,%85,%86,%87,%88,%89,%90,%91,%92,%93,%94,%95,%96,%97,%98,%99,%100,%101,%102,%103,%104,%105,%106,%107,%108,%109,%110,%111,%112,%113,%114,%115,%116,%117,%118,%119,%120,%121,%122,%123,%124,%125,%126,%127}, %128, %129, 1, 1, 1, 0, 1;"
                     : "+f"(d[0]), "+f"(d[1]), "+f"(d[2]), "+f"(d[3]), "+f"(d[4]), "+f"(d[5]), "+f"(d[6]), "+f"(d[7]), "+f"(d[8]), "+f"(d[9]), "+f"(d[10]), "+f"(d[11]), "+f"(d[12]), "+f"(d[13]), "+f"(d[14]), "+f"(d[15]), "+f"(d[16]), "+f"(d[17]), "+f"(d[18]), "+f"(d[19]), "+f"(d[20]), "+f"(d[21]), "+f"(d[22]), "+f"(d[23]), "+f"(d[24]), "+f"(d[25]), "+f"(d[26]), "+f"(d[27]), "+f"(d[28]), "+f"(d[29]), "+f"(d[30]), "+f"(d[31]), "+f"(d[32]), "+f"(d[33]), "+f"(d[34]), "+f"(d[35]), "+f"(d[36]), "+f"(d[37]), "+f"(d[38]), "+f"(d[39]), "+f"(d[40]), "+f"(d[41]), "+f"(d[42]), "+f"(d[43]), "+f"(d[44]), "+f"(d[45]), "+f"(d[46]), "+f"(d[47]), "+f"(d[48]), "+f"(d[49]), "+f"(d[50]), "+f"(d[51]), "+f"(d[52]), "+f"(d[53]), "+f"(d[54]), "+f"(d[55]), "+f"(d[56]), "+f"(d[57]), "+f"(d[58]), "+f"(d[59]), "+f"(d[60]), "+f"(d[61]), "+f"(d[62]), "+f"(d[63]), "+f"(d[64]), "+f"(d[65]), "+f"(d[66]), "+f"(d[67]), "+f"(d[68]), "+f"(d[69]), "+f"(d[70]), "+f"(d[71]), "+f"(d[72]), "+f"(d[73]), "+f"(d[74]), "+f"(d[75]), "+f"(d[76]), "+f"(d[77]), "+f"(d[78]), "+f"(d[79]), "+f"(d[80]), "+f"(d[81]), "+f"(d[82]), "+f"(d[83]), "+f"(d[84]), "+f"(d[85]), "+f"(d[86]), "+f"(d[87]), "+f"(d[88]), "+f"(d[89]), "+f"(d[90]), "+f"(d[91]), "+f"(d[92]), "+f"(d[93]), "+f"(d[94]), "+f"(d[95]), "+f"(d[96]), "+f"(d[97]), "+f"(d[98]), "+f"(d[99]), "+f"(d[100]), "+f"(d[101]), "+f"(d[102]), "+f"(d[103]), "+f"(d[104]), "+f"(d[105]), "+f"(d[106]), "+f"(d[107]), "+f"(d[108]), "+f"(d[109]), "+f"(d[110]), "+f"(d[111]), "+f"(d[112]), "+f"(d[113]), "+f"(d[114]), "+f"(d[115]), "+f"(d[116]), "+f"(d[117]), "+f"(d[118]), "+f"(d[119]), "+f"(d[120]), "+f"(d[121]), "+f"(d[122]), "+f"(d[123]), "+f"(d[124]), "+f"(d[125]), "+f"(d[126]), "+f"(d[127])
                     : "l"(da), "l"(db));
    }
};

__device__ __forceinline__ void mbar_init(uint32_t bar, uint32_t cnt) {
    asm volatile("mbarrier.init.shared::cta.b64 [%0], %1;" ::"r"(bar), "r"(cnt) : "memory");
}
__device__ __forceinline__ void mbar_expect_tx(uint32_t bar, uint32_t bytes) {
    asm volatile("mbarrier.arrive.expect_tx.shared::cta.b64 _, [%0], %1;" ::"r"(bar), "r"(bytes) : "memory");
}
__device__ __forceinline__ void mbar_arrive(uint32_t bar) {
    asm volatile("mbarrier.arrive.shared::cta.b64 _, [%0];" ::"r"(bar) : "memory");
}
__device__ __forceinline__ void mbar_wait(uint32_t bar, uint32_t parity) {
    uint32_t done = 0;
    for (int it = 0; it < (1 << 24) && !done; ++it) {
        asm volatile("{\n .reg .pred p;\n mbarrier.try_wait.parity.shared::cta.b64 p, [%1], %2;\n selp.u32 %0, 1, 0, p;\n}"
                     : "=r"(done) : "r"(bar), "r"(parity) : "memory");
    }
}
__device__ __forceinline__ void tma_load_2d(uint32_t dst, const CUtensorMap* tm, int c0, int c1, uint32_t bar) {
    asm volatile("cp.async.bulk.tensor.2d.shared::cluster.global.mbarrier::complete_tx::bytes [%0], [%1, {%3, %4}], [%2];"
                 ::"r"(dst), "l"(tm), "r"(bar), "r"(c0), "r"(c1) : "memory");
}

constexpr int G_STAGES = 4;
template <int BN> struct GemmCfg {
    static constexpr int NB = (BN + 63) / 64;
    static constexpr int A_BYTES = 128 * 64 * 2;
    static constexpr int B_BYTES = NB * 8192;
    static constexpr int STAGE = A_BYTES + B_BYTES;
    static constexpr int SMEM = G_STAGES * STAGE + 1024 + 256;
};

template <int BN, int KT, int MODE>
__global__ void __launch_bounds__(384, 1)
k_gemm_tc(const __grid_constant__ CUtensorMap tmA, const __grid_constant__ CUtensorMap tmB, bf16* __restrict__ out, int ldo) {
    using C = GemmCfg<BN>;
    extern __shared__ uint8_t gsm[];
    const uint32_t sbase = (smem_u32(gsm) + 1023) & ~1023u;
    const uint32_t bars = sbase + G_STAGES * C::STAGE;
    const int tid = threadIdx.x, wg = tid >> 7;
    const int m0 = blockIdx.y * 128, n0 = blockIdx.x * BN;
    if (tid == 0) {
        for (int i = 0; i < G_STAGES; i++) { mbar_init(bars + 8 * i, 1); mbar_init(bars + 32 + 8 * i, 2); }
        asm volatile("fence.mbarrier_init.release.cluster;" ::: "memory");
    }
    __syncthreads();
    asm volatile("griddepcontrol.wait;" ::: "memory");

    if (wg == 2) {
        if (tid == 256) {
            for (int kt = 0; kt < KT; kt++) {
                const int st = kt % G_STAGES;
                if (kt >= G_STAGES) mbar_wait(bars + 32 + 8 * st, ((kt / G_STAGES) - 1) & 1);
                const uint32_t sa = sbase + st * C::STAGE, sb = sa + C::A_BYTES;
                mbar_expect_tx(bars + 8 * st, C::STAGE);
                tma_load_2d(sa, &tmA, kt * 64, m0, bars + 8 * st);
#pragma unroll
                for (int j = 0; j < C::NB; j++) tma_load_2d(sb + j * 8192, &tmB, n0 + 64 * j, kt * 64, bars + 8 * st);
            }
        }
    } else {
        float acc[BN / 2];
#pragma unroll
        for (int i = 0; i < BN / 2; i++) acc[i] = 0.f;
        constexpr uint64_t DA_HI = ((uint64_t)1 << 16) | ((uint64_t)(1024 >> 4) << 32) | ((uint64_t)1 << 62);
        constexpr uint64_t DB_HI = ((uint64_t)(8192 >> 4) << 16) | ((uint64_t)(1024 >> 4) << 32) | ((uint64_t)1 << 62);
#pragma unroll 1
        for (int kt = 0; kt < KT; kt++) {
            const int st = kt % G_STAGES;
            mbar_wait(bars + 8 * st, (kt / G_STAGES) & 1);
            const uint32_t sa = sbase + st * C::STAGE + wg * 8192, sb = sbase + st * C::STAGE + C::A_BYTES;
            const uint64_t da = DA_HI | (uint64_t)((sa & 0x3FFFF) >> 4);
            const uint64_t db = DB_HI | (uint64_t)((sb & 0x3FFFF) >> 4);
            wg_fence();
#pragma unroll
            for (int k = 0; k < 4; k++) GemmMMA<BN>::run(acc, da + 2 * k, db + 128 * k);
            wg_commit();
            wg_wait<1>();
            if (kt > 0 && (tid & 127) == 0) mbar_arrive(bars + 32 + 8 * ((kt - 1) % G_STAGES));
        }
        wg_wait<0>();
        asm volatile("bar.sync 1, 256;" ::: "memory");
        const int lane = tid & 31, w = (tid >> 5) & 3, g = lane >> 2, t = lane & 3;
        constexpr int PITCH = BN * 2 + 16;
        uint8_t* stg = gsm + (sbase - smem_u32(gsm));
#pragma unroll
        for (int h = 0; h < 2; h++) {
            const int row = wg * 64 + w * 16 + g + 8 * h;
#pragma unroll
            for (int j = 0; j < BN / 8; j++) {
                float v0 = acc[4 * j + 2 * h], v1 = acc[4 * j + 2 * h + 1];
                bf162 o;
                if (MODE == 0) {
                    float h0 = bfr(v0), h1 = bfr(v1);
                    o = __floats2bfloat162_rn(__fdividef(h0, 1.f + __expf(-h0)), __fdividef(h1, 1.f + __expf(-h1)));
                } else {
                    o = __floats2bfloat162_rn(v0, v1);
                }
                *(bf162*)(stg + row * PITCH + (8 * j + 2 * t) * 2) = o;
            }
        }
        asm volatile("bar.sync 1, 256;" ::: "memory");
        constexpr int CPR = BN / 8;
#pragma unroll 2
        for (int idx = tid; idx < 128 * CPR; idx += 256) {
            const int row = idx / CPR, ck = idx % CPR;
            uint4 vv = *(const uint4*)(stg + row * PITCH + ck * 16);
            bf16* dst = out + (size_t)(m0 + row) * ldo + n0 + ck * 8;
            if (MODE == 1) {
                uint4 xv = *(const uint4*)(g_x1 + (size_t)(m0 + row) * D_DIM + n0 + ck * 8);
                const float4* gp = (const float4*)(g_mod + 5 * D_DIM + n0 + ck * 8);
                float4 g0 = gp[0], g1 = gp[1];
                float gbv[8] = {g0.x, g0.y, g0.z, g0.w, g1.x, g1.y, g1.z, g1.w};
                const bf16* po = (const bf16*)&vv;
                const bf16* px = (const bf16*)&xv;
                uint4 r;
                bf16* pr = (bf16*)&r;
#pragma unroll
                for (int e = 0; e < 8; e++) pr[e] = __float2bfloat16_rn(b2f(px[e]) + bfr(gbv[e] * b2f(po[e])));
                vv = r;
            }
            *(uint4*)dst = vv;
        }
    }
}

typedef CUresult (*PFN_encodeTiled)(CUtensorMap*, CUtensorMapDataType, cuuint32_t, void*, const cuuint64_t*, const cuuint64_t*,
                                    const cuuint32_t*, const cuuint32_t*, CUtensorMapInterleave, CUtensorMapSwizzle,
                                    CUtensorMapL2promotion, CUtensorMapFloatOOBfill);

static void make_map(PFN_encodeTiled enc, CUtensorMap* m, const void* ptr, uint64_t inner, uint64_t outer, uint32_t boxi, uint32_t boxo) {
    cuuint64_t dims[2] = {inner, outer};
    cuuint64_t strides[1] = {inner * 2};
    cuuint32_t box[2] = {boxi, boxo};
    cuuint32_t es[2] = {1, 1};
    enc(m, CU_TENSOR_MAP_DATA_TYPE_BFLOAT16, 2, (void*)ptr, dims, strides, box, es, CU_TENSOR_MAP_INTERLEAVE_NONE,
        CU_TENSOR_MAP_SWIZZLE_128B, CU_TENSOR_MAP_L2_PROMOTION_L2_128B, CU_TENSOR_MAP_FLOAT_OOB_FILL_NONE);
}

extern "C" void kernel_launch(void* const* d_in, const int* in_sizes, int n_in,
                              void* d_out, int out_size) {
    const bf16* q = (const bf16*)d_in[0];
    const bf16* k = (const bf16*)d_in[1];
    const bf16* v = (const bf16*)d_in[2];
    const bf16* shift_k = (const bf16*)d_in[3];
    const bf16* ssm_k = (const bf16*)d_in[4];
    const bf16* ssm_D = (const bf16*)d_in[5];
    const bf16* w1 = (const bf16*)d_in[7];
    const bf16* w2 = (const bf16*)d_in[8];
    const bf16* c = (const bf16*)d_in[9];
    const bf16* w_mod = (const bf16*)d_in[10];
    bf16* out = (bf16*)d_out;

    static bool init = false;
    static CUtensorMap tm_h2, tm_w1, tm_h1, tm_w2;
    static bf16 *h2p, *h1p;
    if (!init) {
        cudaFuncSetAttribute(k_conv, cudaFuncAttributeMaxDynamicSharedMemorySize, CONV_SMEM);
        cudaFuncSetAttribute(k_gemm_tc<224, 8, 0>, cudaFuncAttributeMaxDynamicSharedMemorySize, GemmCfg<224>::SMEM);
        cudaFuncSetAttribute(k_gemm_tc<64, 28, 1>, cudaFuncAttributeMaxDynamicSharedMemorySize, GemmCfg<64>::SMEM);
        cudaGetSymbolAddress((void**)&h2p, g_h2);
        cudaGetSymbolAddress((void**)&h1p, g_h1);
        PFN_encodeTiled enc = nullptr;
        cudaDriverEntryPointQueryResult qr;
        cudaGetDriverEntryPoint("cuTensorMapEncodeTiled", (void**)&enc, cudaEnableDefault, &qr);
        make_map(enc, &tm_h2, h2p, D_DIM, S_LEN, 64, 128);
        make_map(enc, &tm_w1, w1, F_DIM, D_DIM, 64, 64);
        make_map(enc, &tm_h1, h1p, F_DIM, S_LEN, 64, 128);
        make_map(enc, &tm_w2, w2, D_DIM, F_DIM, 64, 64);
        init = true;
    }
    k_conv<<<D_DIM / 4, CONV_THREADS, CONV_SMEM>>>(k, v, shift_k, ssm_k, ssm_D, c, w_mod);
    {
        cudaLaunchAttribute at[1];
        at[0].id = cudaLaunchAttributeProgrammaticStreamSerialization;
        at[0].val.programmaticStreamSerializationAllowed = 1;
        cudaLaunchConfig_t cfg = {};
        cfg.stream = cudaStreamPerThread;
        cfg.attrs = at; cfg.numAttrs = 1;
        cfg.gridDim = dim3(S_LEN / MID_ROWS); cfg.blockDim = dim3(512); cfg.dynamicSmemBytes = 0;
        cudaLaunchKernelEx(&cfg, k_mid, q);
        cfg.gridDim = dim3(F_DIM / 224, S_LEN / 128); cfg.blockDim = dim3(384); cfg.dynamicSmemBytes = GemmCfg<224>::SMEM;
        cudaLaunchKernelEx(&cfg, k_gemm_tc<224, 8, 0>, tm_h2, tm_w1, h1p, (int)F_DIM);
        cfg.gridDim = dim3(D_DIM / 64, S_LEN / 128); cfg.dynamicSmemBytes = GemmCfg<64>::SMEM;
        cudaLaunchKernelEx(&cfg, k_gemm_tc<64, 28, 1>, tm_h1, tm_w2, out, (int)D_DIM);
    }
}
```
